```python
import torch

def _softmax(x, axis=-1):
    return torch.softmax(x, dim=axis)
def _gelu(x):
    return torch.nn.functional.gelu(x, approximate="tanh")
def _silu(x):
    return torch.nn.functional.silu(x)
def _sigmoid(x):
    return torch.sigmoid(x)
def _layernorm(x, axis=-1, eps=1e-5):
    m = x.mean(dim=axis, keepdim=True)
    v = x.var(dim=axis, keepdim=True, unbiased=False)
    return (x - m) / torch.sqrt(v + eps)
def _scatter_add(tgt, idx, src, axis=0):
    return tgt.clone().index_add_(axis, idx, src)
def _segment_sum(src, seg, n):
    out = torch.zeros((n,) + src.shape[1:], dtype=src.dtype)
    return out.index_add_(0, seg, src)
def _pad(x, pw):
    flat = tuple(v for pair in reversed(pw) for v in pair)
    return torch.nn.functional.pad(x, flat)

kernel_name = 'recurrent_scan__gqa_block_cached__dense_activation_gelu__decode'

def setup_inputs():

    _w = (lambda a: (lambda t: t.to(torch.bfloat16) if t.is_floating_point() else t)(torch.as_tensor(a)))
    def _A_setup():
        B, Sq, D = 8, 1, 512
        Hq, Hkv, Sk, Dh = 32, 8, 4096, 128
        assert Hq % Hkv == 0, (Hq, Hkv)
        return {
            "x": _w((lambda *s: torch.randn(*s, dtype=torch.bfloat16) * 0.05)(B, Sq, D)),
            "k_cache": _w((lambda *s: torch.randn(*s, dtype=torch.bfloat16) * 3.2)(B, Hkv, Sk, Dh)),
            "v_cache": _w((lambda *s: torch.randn(*s, dtype=torch.bfloat16) * 3.2)(B, Hkv, Sk, Dh)),
            "wq": _w((lambda *s: torch.randn(*s, dtype=torch.bfloat16) * 3.2)(D, Hq * Dh) * (D ** -0.5)),
            "wo": _w((lambda *s: torch.randn(*s, dtype=torch.bfloat16) * 3.2)(Hq * Dh, D) * ((Hq * Dh) ** -0.5)),
        }
    _A_in = _A_setup()

    def _B_setup():
        B, S, D, F = 8, 1, 512, 1792
        return {
            "x": _w((lambda *s: torch.randn(*s, dtype=torch.bfloat16) * 0.05)(B, S, D)),
            "w1": _w((lambda *s: torch.randn(*s, dtype=torch.bfloat16) * 3.2)(D, F) * (D ** -0.5)),
            "b1": _w((lambda *s: torch.randn(*s, dtype=torch.bfloat16) * 3.2)(F) * 0.01),
            "w2": _w((lambda *s: torch.randn(*s, dtype=torch.bfloat16) * 0.4)(F, D) * (F ** -0.5)),
            "b2": _w((lambda *s: torch.randn(*s, dtype=torch.bfloat16) * 0.4)(D) * 0.01),
        }
    _B_in = _B_setup()

    return {
        "A_x": _A_in["x"],
        "A_k_cache": _A_in["k_cache"],
        "A_v_cache": _A_in["v_cache"],
        "A_wq": _A_in["wq"],
        "A_wo": _A_in["wo"],
        "B_x": _B_in["x"],
        "B_w1": _B_in["w1"],
        "B_b1": _B_in["b1"],
        "B_w2": _B_in["w2"],
        "B_b2": _B_in["b2"],
    }

def reference(A_x, A_k_cache, A_v_cache, A_wq, A_wo, B_x, B_w1, B_b1, B_w2, B_b2):
    def _A_ref(x, k_cache, v_cache, wq, wo):
        B, Sq, D = x.shape
        Hq, Dh = 32, 128
        Hkv = k_cache.shape[1]
        rep = Hq // Hkv
        q = (lambda x, *d: x.permute(*d))((x @ wq).reshape(B, Sq, Hq, Dh), 0, 2, 1, 3)
        k = (lambda x, n, axis: torch.repeat_interleave(x, n, dim=axis))(k_cache, rep, axis=1)
        v = (lambda x, n, axis: torch.repeat_interleave(x, n, dim=axis))(v_cache, rep, axis=1)
        scores = torch.einsum("bhqd,bhkd->bhqk", q, k) * (Dh ** -0.5)
        p = _softmax(scores, axis=-1)
        o = torch.einsum("bhqk,bhkd->bhqd", p, v)
        return (lambda x, *d: x.permute(*d))(o, 0, 2, 1, 3).reshape(B, Sq, Hq * Dh) @ wo

    def _B_ref(x, w1, b1, w2, b2):
        h = torch.einsum("bsd,df->bsf", x, w1) + b1
        h = _gelu(h)
        return torch.einsum("bsf,fd->bsd", h, w2) + b2

    x = A_x
    xn = _layernorm(x, axis=-1)
    s = _A_ref(xn, A_k_cache, A_v_cache, A_wq, A_wo)
    g = _silu(_B_ref(xn, B_w1, B_b1, B_w2, B_b2))
    return x + s * g
```

```cpp
#include <cuda_runtime.h>
#include <cuda_bf16.h>
#include <cuda.h>
#include <stdint.h>

namespace {

constexpr int NB = 8, DM = 512, HQ = 32, HKV = 8, SK = 4096, DH = 128, FF = 1792;
constexpr int N_ATT = 128, N_FFN = 4, N_CTA = N_ATT + N_FFN;
constexpr int THREADS = 192;
#define STAGES_ 12
#define INFLIGHT_ 7
constexpr int STAGES = STAGES_;
constexpr int INFLIGHT = INFLIGHT_;
constexpr int STAGE_BYTES = 16384;
constexpr int KV_TILES = 32;
constexpr int NT_ATT = 2 + 2 * KV_TILES + 2;
constexpr int W1_TILES = 32, W2_TILES = 28, NT_FFN = W1_TILES + W2_TILES;
constexpr int W1_BYTES = 7 * 16 * 128;
constexpr int FS = FF / N_FFN;
constexpr int XN_STRIDE = DM + 8;
constexpr int H_STRIDE = FS + 8;

constexpr int SM_RING = 0;
constexpr int SM_XN = SM_RING + STAGES * STAGE_BYTES;
constexpr int SM_RED = SM_XN + NB * XN_STRIDE * 2;
constexpr int SM_INO = SM_RED + 7424;
constexpr int SM_INML = SM_INO + 8192;
constexpr int SM_BAR = SM_INML + 128;
constexpr int SM_END = SM_BAR + (2 * STAGES + 4) * 8;
constexpr int SMEM_BYTES = SM_END + 1024;
static_assert(SMEM_BYTES <= 232448, "smem");
static_assert(SM_INO % 16 == 0 && SM_BAR % 8 == 0, "align");

__device__ uint32_t g_q[HKV * NB * 16 * 16];
__device__ uint32_t g_o[NB * HQ * 64];
__device__ uint32_t g_s[NB * 16 * HQ * 32];
__device__ uint32_t g_gp[N_FFN * NB * DM];
__device__ unsigned g_ctr;

#define STAMP(k) do {} while (0)

constexpr int SPIN_LIMIT = 1 << 22;

__device__ __forceinline__ uint32_t smem_u32(const void* p) { return (uint32_t)__cvta_generic_to_shared(p); }
__device__ __forceinline__ void mbar_init(uint32_t bar, uint32_t cnt) {
    asm volatile("mbarrier.init.shared::cta.b64 [%0], %1;" ::"r"(bar), "r"(cnt) : "memory");
}
__device__ __forceinline__ void mbar_expect_tx(uint32_t bar, uint32_t bytes) {
    asm volatile("mbarrier.arrive.expect_tx.shared::cta.b64 _, [%0], %1;" ::"r"(bar), "r"(bytes) : "memory");
}
__device__ __forceinline__ void mbar_arrive(uint32_t bar) {
    asm volatile("mbarrier.arrive.shared::cta.b64 _, [%0];" ::"r"(bar) : "memory");
}
__device__ __forceinline__ void mbar_wait(uint32_t bar, uint32_t parity) {
    uint32_t ok;
    int it = 0;
    do {
        asm volatile("{\n.reg .pred p;\nmbarrier.try_wait.parity.shared::cta.b64 p, [%1], %2;\nselp.u32 %0, 1, 0, p;\n}"
                     : "=r"(ok) : "r"(bar), "r"(parity) : "memory");
        if (++it > SPIN_LIMIT) __trap();
    } while (!ok);
}
__device__ __forceinline__ void mbar_wait_cluster(uint32_t bar, uint32_t parity) {
    uint32_t ok;
    int it = 0;
    do {
        asm volatile("{\n.reg .pred p;\nmbarrier.try_wait.parity.acquire.cluster.shared::cta.b64 p, [%1], %2;\nselp.u32 %0, 1, 0, p;\n}"
                     : "=r"(ok) : "r"(bar), "r"(parity) : "memory");
        if (++it > SPIN_LIMIT) __trap();
    } while (!ok);
}
__device__ __forceinline__ void tma2d(uint32_t dst, const CUtensorMap* m, uint32_t bar, int c0, int c1) {
    asm volatile("cp.async.bulk.tensor.2d.shared::cluster.global.mbarrier::complete_tx::bytes [%0], [%1, {%3, %4}], [%2];"
                 ::"r"(dst), "l"(m), "r"(bar), "r"(c0), "r"(c1) : "memory");
}
__device__ __forceinline__ void tma3d(uint32_t dst, const CUtensorMap* m, uint32_t bar, int c0, int c1, int c2, uint64_t pol) {
    asm volatile("cp.async.bulk.tensor.3d.shared::cluster.global.mbarrier::complete_tx::bytes.L2::cache_hint [%0], [%1, {%3, %4, %5}], [%2], %6;"
                 ::"r"(dst), "l"(m), "r"(bar), "r"(c0), "r"(c1), "r"(c2), "l"(pol) : "memory");
}
__device__ __forceinline__ void tma5d(uint32_t dst, const CUtensorMap* m, uint32_t bar, int c3, int c4, uint64_t pol) {
    asm volatile("cp.async.bulk.tensor.5d.shared::cluster.global.mbarrier::complete_tx::bytes.L2::cache_hint [%0], [%1, {%3, %3, %3, %4, %5}], [%2], %6;"
                 ::"r"(dst), "l"(m), "r"(bar), "r"(0), "r"(c3), "r"(c4), "l"(pol) : "memory");
}
__device__ __forceinline__ void ldsm4(uint32_t (&r)[4], uint32_t addr) {
    asm volatile("ldmatrix.sync.aligned.m8n8.x4.shared.b16 {%0, %1, %2, %3}, [%4];"
                 : "=r"(r[0]), "=r"(r[1]), "=r"(r[2]), "=r"(r[3]) : "r"(addr) : "memory");
}
__device__ __forceinline__ void ldsm4t(uint32_t (&r)[4], uint32_t addr) {
    asm volatile("ldmatrix.sync.aligned.m8n8.x4.trans.shared.b16 {%0, %1, %2, %3}, [%4];"
                 : "=r"(r[0]), "=r"(r[1]), "=r"(r[2]), "=r"(r[3]) : "r"(addr) : "memory");
}
__device__ __forceinline__ void mma16816(float (&c)[4], const uint32_t (&a)[4], uint32_t b0, uint32_t b1) {
    asm volatile("mma.sync.aligned.m16n8k16.row.col.f32.bf16.bf16.f32 {%0, %1, %2, %3}, {%4, %5, %6, %7}, {%8, %9}, {%0, %1, %2, %3};"
                 : "+f"(c[0]), "+f"(c[1]), "+f"(c[2]), "+f"(c[3])
                 : "r"(a[0]), "r"(a[1]), "r"(a[2]), "r"(a[3]), "r"(b0), "r"(b1));
}
__device__ __forceinline__ uint32_t movm_t(uint32_t a) {
    uint32_t d;
    asm volatile("movmatrix.sync.aligned.m8n8.trans.b16 %0, %1;" : "=r"(d) : "r"(a));
    return d;
}
__device__ __forceinline__ uint32_t pack_bf16(float lo, float hi) {
    uint32_t d;
    asm("cvt.rn.bf16x2.f32 %0, %1, %2;" : "=r"(d) : "f"(hi), "f"(lo));
    return d;
}
__device__ __forceinline__ float bf_lo(uint32_t v) { return __uint_as_float(v << 16); }
__device__ __forceinline__ float bf_hi(uint32_t v) { return __uint_as_float(v & 0xffff0000u); }
__device__ __forceinline__ float rbf(float x) { return __bfloat162float(__float2bfloat16_rn(x)); }
__device__ __forceinline__ uint32_t max_bf16x2(uint32_t a, uint32_t b) {
    uint32_t d;
    asm("max.bf16x2 %0, %1, %2;" : "=r"(d) : "r"(a), "r"(b));
    return d;
}
__device__ __forceinline__ float ex2(float x) {
    float y;
    asm("ex2.approx.ftz.f32 %0, %1;" : "=f"(y) : "f"(x));
    return y;
}
__device__ __forceinline__ uint32_t nz(uint32_t w) { return w == 0u ? 0x80000000u : w; }
__device__ __forceinline__ void st_rlx(uint32_t* p, uint32_t v) {
    asm volatile("st.relaxed.gpu.global.u32 [%0], %1;" ::"l"(p), "r"(v) : "memory");
}
__device__ __forceinline__ void st_rlx_zero4(uint32_t* p) {
    asm volatile("st.relaxed.gpu.global.v4.u32 [%0], {%1, %1, %1, %1};" ::"l"(p), "r"(0) : "memory");
}
__device__ __forceinline__ uint32_t ld_rlx(const uint32_t* p) {
    uint32_t v;
    asm volatile("ld.relaxed.gpu.global.u32 %0, [%1];" : "=r"(v) : "l"(p) : "memory");
    return v;
}
__device__ __forceinline__ uint4 ld_rlx4(const uint32_t* p) {
    uint4 v;
    asm volatile("ld.relaxed.gpu.global.v4.u32 {%0, %1, %2, %3}, [%4];" : "=r"(v.x), "=r"(v.y), "=r"(v.z), "=r"(v.w) : "l"(p) : "memory");
    return v;
}
__device__ __forceinline__ bool all_set(const uint4& v) { return v.x != 0u && v.y != 0u && v.z != 0u && v.w != 0u; }
__device__ __forceinline__ void st_async4(uint32_t addr, float a, float b, float c, float d, uint32_t bar) {
    asm volatile("st.async.shared::cluster.mbarrier::complete_tx::bytes.v4.f32 [%0], {%1, %2, %3, %4}, [%5];"
                 ::"r"(addr), "f"(a), "f"(b), "f"(c), "f"(d), "r"(bar) : "memory");
}
__device__ __forceinline__ uint32_t mapa(uint32_t addr, uint32_t rank) {
    uint32_t r;
    asm("mapa.shared::cluster.u32 %0, %1, %2;" : "=r"(r) : "r"(addr), "r"(rank));
    return r;
}
__device__ __forceinline__ void cluster_arrive_relaxed() { asm volatile("barrier.cluster.arrive.relaxed.aligned;" ::: "memory"); }
__device__ __forceinline__ void cluster_wait() { asm volatile("barrier.cluster.wait.aligned;" ::: "memory"); }
__device__ __forceinline__ void bar_compute() { asm volatile("bar.sync 1, 128;" ::: "memory"); }

struct Cursor {
    int slot = 0;
    uint32_t phase = 0;
    __device__ __forceinline__ void next() { if (++slot == STAGES) { slot = 0; phase ^= 1u; } }
};

constexpr float LOG2E = 1.4426950408889634f;

__global__ void __cluster_dims__(2, 1, 1) __launch_bounds__(THREADS, 1)
fused_decode_kernel(const __grid_constant__ CUtensorMap mapK, const __grid_constant__ CUtensorMap mapV,
                    const __grid_constant__ CUtensorMap mapWq, const __grid_constant__ CUtensorMap mapWo,
                    const __grid_constant__ CUtensorMap mapW1, const __grid_constant__ CUtensorMap mapW2,
                    const __nv_bfloat16* __restrict__ x, const __nv_bfloat16* __restrict__ b1,
                    const __nv_bfloat16* __restrict__ b2, __nv_bfloat16* __restrict__ out) {
    extern __shared__ uint8_t smem_raw[];
    const uint32_t sb = (smem_u32(smem_raw) + 1023u) & ~1023u;
    uint8_t* sp = smem_raw + (sb - smem_u32(smem_raw));
    const uint32_t bar_full = sb + SM_BAR, bar_empty = bar_full + 8 * STAGES;
    const uint32_t bar_ml = bar_empty + 8 * STAGES, bar_o = bar_ml + 8, bar_ok = bar_o + 8;

    const int tid = threadIdx.x, warp = tid >> 5, lane = tid & 31;
    const int cta = blockIdx.x;
    const bool is_att = cta < N_ATT;
    const int bh = cta >> 1, rank = cta & 1;
    const int b = bh >> 3, hkv = bh & 7;
    const int j = 2 * b + rank;
    const int hh = 4 * hkv + (j >> 2);
    const int f = cta - N_ATT;

    if (warp == 4) {
        if (lane == 0) STAMP(0);
        if (lane < STAGES) {
            mbar_init(bar_full + 8 * lane, 1);
            mbar_init(bar_empty + 8 * lane, 4);
        } else if (lane < STAGES + 3) {
            mbar_init(bar_ml + 8 * (lane - STAGES), 1);
        }
        asm volatile("fence.mbarrier_init.release.cluster;" ::: "memory");
        __syncwarp();
        cluster_arrive_relaxed();
        if (lane == 0) {
            uint64_t pol;
            asm volatile("createpolicy.fractional.L2::evict_first.b64 %0, 1.0;" : "=l"(pol));
            const int nt = is_att ? NT_ATT : NT_FFN;
            const int row0 = bh * SK + rank * (SK / 2);
            Cursor cur, lag;
            for (int i = 0; i < nt; i++) {
                if (i >= STAGES) mbar_wait(bar_empty + 8 * cur.slot, cur.phase ^ 1u);
                if (INFLIGHT < STAGES && i >= INFLIGHT) { mbar_wait(bar_full + 8 * lag.slot, lag.phase); lag.next(); }
                const uint32_t dst = sb + SM_RING + cur.slot * STAGE_BYTES, bar = bar_full + 8 * cur.slot;
                if (is_att) {
                    mbar_expect_tx(bar, STAGE_BYTES);
                    if (i < 2) tma2d(dst, &mapWq, bar, hkv * 512 + 32 * j, 256 * i);
                    else if (i < NT_ATT - 2) tma3d(dst, (i & 1) ? &mapV : &mapK, bar, 0, row0 + ((i - 2) >> 1) * 64, 0, pol);
                    else tma5d(dst, &mapWo, bar, hh * 8 + 4 * (i - (NT_ATT - 2)), 2 * (j & 3), pol);
                } else {
                    if (i < W1_TILES) { mbar_expect_tx(bar, W1_BYTES); tma3d(dst, &mapW1, bar, 0, 16 * i, 7 * f, pol); }
                    else { mbar_expect_tx(bar, STAGE_BYTES); tma3d(dst, &mapW2, bar, 0, FS * f + 16 * (i - W1_TILES), 0, pol); }
                }
                if (i == 1 && is_att) { mbar_expect_tx(bar_ml, 8 * 16); mbar_expect_tx(bar_o, 8 * 1024); }
                cur.next();
            }
            STAMP(1);
        }
        __syncwarp();
        cluster_wait();
    } else if (warp == 5) {
        cluster_arrive_relaxed();
        const int fb = cta >> 4, fcb = cta & 15;
        uint32_t* inbox = g_s + (fb * 16 + fcb) * (HQ * 32);
        if (is_att) {
            st_rlx_zero4(g_o + (b * HQ + 4 * hkv + 2 * rank) * 64 + lane * 4);
#pragma unroll
            for (int i = 0; i < 8; i++) st_rlx_zero4(inbox + i * 128 + lane * 4);
        } else {
#pragma unroll 4
            for (int i = 0; i < 32; i++) st_rlx_zero4(g_gp + f * (NB * DM) + i * 128 + lane * 4);
        }
        __syncwarp();
        if (lane == 0) {
            __threadfence();
            atomicInc(&g_ctr, N_CTA - 1);
        }
        __syncwarp();
        cluster_wait();
        if (lane == 0) {
            int it = 0;
            while (true) {
                unsigned v;
                asm volatile("ld.acquire.gpu.global.u32 %0, [%1];" : "=r"(v) : "l"(&g_ctr) : "memory");
                if (v == 0u) break;
                __nanosleep(500);
                if (++it > SPIN_LIMIT) __trap();
            }
            mbar_arrive(bar_ok);
        }
        __syncwarp();
        if (is_att) {
            const int col = fcb * 32 + 4 * (lane & 7) + (lane >> 3);
            const float xv = __bfloat162float(x[fb * DM + col]);
            const float b2v = __bfloat162float(b2[col]);
            uint32_t p0, p1, p2, p3;
            int it = 0;
            while (true) {
                p0 = ld_rlx(g_gp + 0 * (NB * DM) + fb * DM + col);
                p1 = ld_rlx(g_gp + 1 * (NB * DM) + fb * DM + col);
                p2 = ld_rlx(g_gp + 2 * (NB * DM) + fb * DM + col);
                p3 = ld_rlx(g_gp + 3 * (NB * DM) + fb * DM + col);
                if (__all_sync(0xffffffffu, p0 != 0u && p1 != 0u && p2 != 0u && p3 != 0u)) break;
                __nanosleep(1000);
                if (++it > SPIN_LIMIT) __trap();
            }
            float y = rbf((__uint_as_float(p0) + __uint_as_float(p1)) + (__uint_as_float(p2) + __uint_as_float(p3)));
            y = rbf(y + b2v);
            const float gate = rbf(y / (1.0f + expf(-y)));
            if (lane == 0) STAMP(8);
            mbar_wait(bar_o, 0);
            uint4 v[8];
            it = 0;
            while (true) {
                bool ok = true;
#pragma unroll
                for (int i = 0; i < 8; i++) v[i] = ld_rlx4(inbox + i * 128 + lane * 4);
#pragma unroll
                for (int i = 0; i < 8; i++) ok = ok && all_set(v[i]);
                if (__all_sync(0xffffffffu, ok)) break;
                if (++it > SPIN_LIMIT) __trap();
            }
            float s0 = 0.f, s1 = 0.f, s2 = 0.f, s3 = 0.f;
#pragma unroll
            for (int i = 0; i < 8; i++) {
                s0 += __uint_as_float(v[i].x); s1 += __uint_as_float(v[i].y);
                s2 += __uint_as_float(v[i].z); s3 += __uint_as_float(v[i].w);
            }
            const bool up = lane & 16;
            float k0 = up ? s2 : s0, k1 = up ? s3 : s1;
            k0 += __shfl_xor_sync(0xffffffffu, up ? s0 : s2, 16);
            k1 += __shfl_xor_sync(0xffffffffu, up ? s1 : s3, 16);
            const bool odd = lane & 8;
            float s = odd ? k1 : k0;
            s += __shfl_xor_sync(0xffffffffu, odd ? k0 : k1, 8);
            out[fb * DM + col] = __float2bfloat16_rn(xv + rbf(rbf(s) * gate));
            if (lane == 0) STAMP(9);
        }
    } else {
        cluster_arrive_relaxed();
        const int g = lane >> 2, t = lane & 3;
        {
            uint4 xv[2][2];
#pragma unroll
            for (int r = 0; r < 2; r++)
#pragma unroll
                for (int h = 0; h < 2; h++)
                    xv[r][h] = __ldg(reinterpret_cast<const uint4*>(x + (2 * warp + r) * DM + h * 256 + lane * 8));
#pragma unroll
            for (int r = 0; r < 2; r++) {
                float v[16];
#pragma unroll
                for (int h = 0; h < 2; h++) {
                    const uint32_t w4[4] = {xv[r][h].x, xv[r][h].y, xv[r][h].z, xv[r][h].w};
#pragma unroll
                    for (int i = 0; i < 4; i++) { v[h * 8 + 2 * i] = bf_lo(w4[i]); v[h * 8 + 2 * i + 1] = bf_hi(w4[i]); }
                }
                float sum = 0.f;
#pragma unroll
                for (int i = 0; i < 16; i++) sum += v[i];
#pragma unroll
                for (int o = 16; o > 0; o >>= 1) sum += __shfl_xor_sync(0xffffffffu, sum, o);
                const float mean = sum * (1.0f / DM);
                float sq = 0.f;
#pragma unroll
                for (int i = 0; i < 16; i++) { const float d = v[i] - mean; sq += d * d; }
#pragma unroll
                for (int o = 16; o > 0; o >>= 1) sq += __shfl_xor_sync(0xffffffffu, sq, o);
                const float mb = rbf(mean);
                const float sd = rbf(sqrtf(rbf(rbf(sq * (1.0f / DM)) + 1e-5f)));
#pragma unroll
                for (int h = 0; h < 2; h++) {
                    uint4 o4;
                    uint32_t w4[4];
#pragma unroll
                    for (int i = 0; i < 4; i++)
                        w4[i] = pack_bf16(rbf(v[h * 8 + 2 * i] - mb) / sd, rbf(v[h * 8 + 2 * i + 1] - mb) / sd);
                    o4.x = w4[0]; o4.y = w4[1]; o4.z = w4[2]; o4.w = w4[3];
                    *reinterpret_cast<uint4*>(sp + SM_XN + ((2 * warp + r) * XN_STRIDE + h * 256 + lane * 8) * 2) = o4;
                }
            }
        }
        cluster_wait();
        bar_compute();
        const uint32_t* xn32 = reinterpret_cast<const uint32_t*>(sp + SM_XN) + g * (XN_STRIDE / 2) + t;
        const int krow = (lane & 7) + (lane >> 4) * 8;
        const int cbit = (lane >> 3) & 1;
        Cursor cur;

        if (is_att) {
            uint32_t* qword;
            {
                float acc[2][4] = {};
                const int st = warp >> 1;
                mbar_wait(bar_full + 8 * st, 0);
                if (tid == 0) STAMP(2);
                const uint32_t base = sb + SM_RING + st * STAGE_BYTES + ((warp & 1) * 128 + krow) * 64;
                const int sw = (krow >> 1) & 3;
#pragma unroll
                for (int ks = 0; ks < 8; ks++) {
                    const uint32_t b0 = xn32[warp * 64 + ks * 8], b1r = xn32[warp * 64 + ks * 8 + 4];
#pragma unroll
                    for (int mt = 0; mt < 2; mt++) {
                        uint32_t a[4];
                        ldsm4t(a, base + ks * 1024 + (((2 * mt + cbit) ^ sw) << 4));
                        mma16816(acc[mt], a, b0, b1r);
                    }
                }
                __syncwarp();
                if (lane == 0) { mbar_arrive(bar_empty); mbar_arrive(bar_empty + 8); }
                cur.next(); cur.next();
                float* red = reinterpret_cast<float*>(sp + SM_RED);
#pragma unroll
                for (int mt = 0; mt < 2; mt++) {
                    red[(warp * 8 + 2 * t) * 36 + 16 * mt + g] = acc[mt][0];
                    red[(warp * 8 + 2 * t + 1) * 36 + 16 * mt + g] = acc[mt][1];
                    red[(warp * 8 + 2 * t) * 36 + 16 * mt + g + 8] = acc[mt][2];
                    red[(warp * 8 + 2 * t + 1) * 36 + 16 * mt + g + 8] = acc[mt][3];
                }
                bar_compute();
                const int qb = tid >> 4, pos = tid & 15;
                const int col = 8 * (pos & 3) + 2 * (pos >> 2);
                float s0 = 0.f, s1 = 0.f;
#pragma unroll
                for (int w = 0; w < 4; w++) {
                    const float2 v = *reinterpret_cast<const float2*>(red + (w * 8 + qb) * 36 + col);
                    s0 += v.x; s1 += v.y;
                }
                qword = g_q + ((hkv * NB + qb) * 16 + j) * 16 + pos;
                st_rlx(qword, nz(pack_bf16(s0, s1)));
            }
            uint32_t qf[8][2];
            {
                uint4 v[4] = {};
                if (g < 4) {
                    const uint32_t* src = g_q + ((hkv * NB + b) * 16 + 4 * g) * 16 + 4 * t;
                    int it = 0;
                    while (true) {
#pragma unroll
                        for (int i = 0; i < 4; i++) v[i] = ld_rlx4(src + 16 * i);
                        if (all_set(v[0]) && all_set(v[1]) && all_set(v[2]) && all_set(v[3])) break;
                        if (++it > SPIN_LIMIT) __trap();
                    }
                }
                __syncwarp();
#pragma unroll
                for (int i = 0; i < 4; i++) {
                    qf[2 * i][0] = v[i].x; qf[2 * i][1] = v[i].y;
                    qf[2 * i + 1][0] = v[i].z; qf[2 * i + 1][1] = v[i].w;
                }
            }
            if (tid == 0) STAMP(3);
            float o[8][4] = {};
            float m0 = -INFINITY, m1 = -INFINITY, l0 = 0.f, l1 = 0.f;
            uint32_t mpk = 0xff80ff80u;
            uint32_t koff[4], voff[4];
#pragma unroll
            for (int i = 0; i < 4; i++) {
                koff[i] = (16 * warp + (lane & 7) + cbit * 8) * 128 + (((2 * i + (lane >> 4)) ^ (lane & 7)) << 4);
                voff[i] = (16 * warp + krow) * 128 + (((2 * i + cbit) ^ (lane & 7)) << 4);
            }
            const uint32_t dst_rank = t & 1;
            const uint32_t r_ml = mapa(sb + SM_INML + (rank * 4 + warp) * 16, dst_rank);
            const uint32_t r_o = mapa(sb + SM_INO + (rank * 4 + warp) * 1024 + (g & 3) * 256, dst_rank);
            const uint32_t r_bar_ml = mapa(bar_ml, dst_rank), r_bar_o = mapa(bar_o, dst_rank);
#pragma unroll 1
            for (int tile = 0; tile < KV_TILES; tile++) {
                mbar_wait(bar_full + 8 * cur.slot, cur.phase);
                uint32_t base = sb + SM_RING + cur.slot * STAGE_BYTES;
                float sa[4] = {}, sc[4] = {};
#pragma unroll
                for (int i = 0; i < 4; i++) {
                    uint32_t a0[4], a1[4];
                    ldsm4(a0, base + koff[i]);
                    ldsm4(a1, base + 8192 + koff[i]);
                    mma16816(sa, a0, qf[i][0], qf[i][1]);
                    mma16816(sc, a1, qf[4 + i][0], qf[4 + i][1]);
                }
                __syncwarp();
                if (lane == 0) mbar_arrive(bar_empty + 8 * cur.slot);
                cur.next();
                uint32_t s01 = pack_bf16(sa[0] + sc[0], sa[1] + sc[1]);
                uint32_t s23 = pack_bf16(sa[2] + sc[2], sa[3] + sc[3]);
                const float scale = 0.08838834764831845f;
                s01 = pack_bf16(bf_lo(s01) * scale, bf_hi(s01) * scale);
                s23 = pack_bf16(bf_lo(s23) * scale, bf_hi(s23) * scale);
                uint32_t mx = max_bf16x2(s01, s23);
                mx = max_bf16x2(mx, __shfl_xor_sync(0xffffffffu, mx, 4));
                mx = max_bf16x2(mx, __shfl_xor_sync(0xffffffffu, mx, 8));
                mx = max_bf16x2(mx, __shfl_xor_sync(0xffffffffu, mx, 16));
                mx = max_bf16x2(mx, mpk);
                if (__any_sync(0xffffffffu, mx != mpk)) {
                    const float n0 = bf_lo(mx), n1 = bf_hi(mx);
                    const float a0 = ex2((m0 - n0) * LOG2E), a1 = ex2((m1 - n1) * LOG2E);
                    m0 = n0; m1 = n1; mpk = mx;
                    l0 *= a0; l1 *= a1;
#pragma unroll
                    for (int mt = 0; mt < 8; mt++) { o[mt][0] *= a0; o[mt][1] *= a1; o[mt][2] *= a0; o[mt][3] *= a1; }
                }
                const float p0 = ex2((bf_lo(s01) - m0) * LOG2E), p1 = ex2((bf_hi(s01) - m1) * LOG2E);
                const float p2 = ex2((bf_lo(s23) - m0) * LOG2E), p3 = ex2((bf_hi(s23) - m1) * LOG2E);
                l0 += p0 + p2; l1 += p1 + p3;
                const uint32_t pb0 = movm_t(pack_bf16(p0, p1)), pb1 = movm_t(pack_bf16(p2, p3));
                if (tile == KV_TILES - 1) {
                    mbar_wait(bar_ok, 0);
#pragma unroll
                    for (int of = 4; of < 32; of <<= 1) {
                        l0 += __shfl_xor_sync(0xffffffffu, l0, of);
                        l1 += __shfl_xor_sync(0xffffffffu, l1, of);
                    }
                    if (lane < 2) st_async4(r_ml, m0, l0, m1, l1, r_bar_ml);
                }
                mbar_wait(bar_full + 8 * cur.slot, cur.phase);
                base = sb + SM_RING + cur.slot * STAGE_BYTES;
#pragma unroll
                for (int i = 0; i < 4; i++) {
                    uint32_t a0[4], a1[4];
                    ldsm4t(a0, base + voff[i]);
                    ldsm4t(a1, base + 8192 + voff[i]);
                    mma16816(o[i], a0, pb0, pb1);
                    mma16816(o[4 + i], a1, pb0, pb1);
                }
                __syncwarp();
                if (lane == 0) mbar_arrive(bar_empty + 8 * cur.slot);
                cur.next();
            }
            if (tid == 0) STAMP(4);
            if (t < 2) {
#pragma unroll
                for (int mt = 0; mt < 8; mt++)
                    st_async4(r_o + (((2 * mt + (g >> 2) + 2 * (g & 3)) & 15) << 4), o[mt][0], o[mt][2], o[mt][1], o[mt][3], r_bar_o);
            }
            {
                const int hp = tid & 1, pp = tid >> 1;
                mbar_wait_cluster(bar_ml, 0);
                float2 ml[8];
#pragma unroll
                for (int s = 0; s < 8; s++) ml[s] = *reinterpret_cast<const float2*>(sp + SM_INML + s * 16 + hp * 8);
                float M = ml[0].x;
#pragma unroll
                for (int s = 1; s < 8; s++) M = fmaxf(M, ml[s].x);
                float fs[8], L = 0.f;
#pragma unroll
                for (int s = 0; s < 8; s++) { fs[s] = ex2((ml[s].x - M) * LOG2E); L += fs[s] * ml[s].y; }
                const float inv = 1.0f / L;
#pragma unroll
                for (int s = 0; s < 8; s++) fs[s] *= inv;
                const int tt = pp >> 4, wi = 16 * tt + (((pp & 15) - 2 * tt) & 15);
                uint32_t* dst = g_o + (b * HQ + 4 * hkv + 2 * rank + hp) * 64 + wi;
                mbar_wait_cluster(bar_o, 0);
                float r0 = 0.f, r1 = 0.f, r2 = 0.f, r3 = 0.f;
#pragma unroll
                for (int s = 0; s < 8; s += 2) {
                    const float2 va = *reinterpret_cast<const float2*>(sp + SM_INO + s * 1024 + tid * 8);
                    const float2 vb = *reinterpret_cast<const float2*>(sp + SM_INO + (s + 1) * 1024 + tid * 8);
                    r0 += fs[s] * va.x; r1 += fs[s] * va.y;
                    r2 += fs[s + 1] * vb.x; r3 += fs[s + 1] * vb.y;
                }
                st_rlx(dst, nz(pack_bf16(r0 + r2, r1 + r3)));
            }
            if (tid == 0) STAMP(5);
            {
                uint32_t wf[8][2][4];
                const uint32_t woff = (warp >> 1) * 8192 + krow * 128;
#pragma unroll
                for (int s = 0; s < 2; s++) {
                    mbar_wait(bar_full + 8 * cur.slot, cur.phase);
                    const uint32_t base = sb + SM_RING + cur.slot * STAGE_BYTES + woff;
#pragma unroll
                    for (int a = 0; a < 4; a++)
#pragma unroll
                        for (int mt = 0; mt < 2; mt++)
                            ldsm4t(wf[4 * s + a][mt], base + a * 2048 + (((4 * (warp & 1) + 2 * mt + cbit) ^ (lane & 7)) << 4));
                    cur.next();
                }
                if (tid == 0) STAMP(6);
                uint4 v[4];
                const uint32_t* src = g_o + (g * HQ + hh) * 64 + 16 * t;
                int it = 0;
                while (true) {
#pragma unroll
                    for (int i = 0; i < 4; i++) v[i] = ld_rlx4(src + 4 * i);
                    if (all_set(v[0]) && all_set(v[1]) && all_set(v[2]) && all_set(v[3])) break;
                    if (++it > SPIN_LIMIT) __trap();
                }
                __syncwarp();
                float acc[2][2][4] = {};
#pragma unroll
                for (int i = 0; i < 4; i++) {
#pragma unroll
                    for (int mt = 0; mt < 2; mt++) {
                        mma16816(acc[0][mt], wf[2 * i][mt], v[i].x, v[i].y);
                        mma16816(acc[1][mt], wf[2 * i + 1][mt], v[i].z, v[i].w);
                    }
                }
                uint32_t* dst = g_s + ((2 * t * 16 + (j & 3) * 4 + warp) * HQ + hh) * 32 + g;
#pragma unroll
                for (int mt = 0; mt < 2; mt++) {
                    st_rlx(dst + 16 * mt, nz(__float_as_uint(acc[0][mt][0] + acc[1][mt][0])));
                    st_rlx(dst + 16 * mt + 16 * HQ * 32, nz(__float_as_uint(acc[0][mt][1] + acc[1][mt][1])));
                    st_rlx(dst + 16 * mt + 8, nz(__float_as_uint(acc[0][mt][2] + acc[1][mt][2])));
                    st_rlx(dst + 16 * mt + 8 + 16 * HQ * 32, nz(__float_as_uint(acc[0][mt][3] + acc[1][mt][3])));
                }
                st_rlx(qword, 0u);
            }
            if (tid == 0) STAMP(7);
        } else {
            float acc[8][4] = {};
#pragma unroll 1
            for (int kt = 0; kt < W1_TILES; kt++) {
                const uint32_t b0 = xn32[kt * 8], b1r = xn32[kt * 8 + 4];
                mbar_wait(bar_full + 8 * cur.slot, cur.phase);
                const uint32_t base = sb + SM_RING + cur.slot * STAGE_BYTES + krow * 128;
#pragma unroll
                for (int i = 0; i < 7; i++) {
                    const int mt = warp * 7 + i;
                    uint32_t a[4];
                    ldsm4t(a, base + (mt >> 2) * 2048 + (((2 * (mt & 3) + cbit) ^ (lane & 7)) << 4));
                    mma16816(acc[i], a, b0, b1r);
                }
                __syncwarp();
                if (lane == 0) mbar_arrive(bar_empty + 8 * cur.slot);
                cur.next();
            }
            __nv_bfloat16* hs = reinterpret_cast<__nv_bfloat16*>(sp + SM_RED);
#pragma unroll
            for (int i = 0; i < 7; i++) {
#pragma unroll
                for (int c = 0; c < 4; c++) {
                    const int u = (warp * 7 + i) * 16 + g + (c >> 1) * 8;
                    const float hv = rbf(rbf(acc[i][c]) + __bfloat162float(b1[FS * f + u]));
                    const float inner = 0.7978845608028654f * (hv + 0.044715f * hv * hv * hv);
                    hs[(2 * t + (c & 1)) * H_STRIDE + u] = __float2bfloat16_rn(0.5f * hv * (1.0f + tanhf(inner)));
                }
            }
            bar_compute();
#pragma unroll
            for (int i = 0; i < 8; i++) { acc[i][0] = 0.f; acc[i][1] = 0.f; acc[i][2] = 0.f; acc[i][3] = 0.f; }
            const uint32_t* h32 = reinterpret_cast<const uint32_t*>(sp + SM_RED) + g * (H_STRIDE / 2) + t;
#pragma unroll 1
            for (int kt = 0; kt < W2_TILES; kt++) {
                const uint32_t b0 = h32[kt * 8], b1r = h32[kt * 8 + 4];
                mbar_wait(bar_full + 8 * cur.slot, cur.phase);
                const uint32_t base = sb + SM_RING + cur.slot * STAGE_BYTES + krow * 128 + warp * 4096;
#pragma unroll
                for (int i = 0; i < 8; i++) {
                    uint32_t a[4];
                    ldsm4t(a, base + (i >> 2) * 2048 + (((2 * (i & 3) + cbit) ^ (lane & 7)) << 4));
                    mma16816(acc[i], a, b0, b1r);
                }
                __syncwarp();
                if (lane == 0) mbar_arrive(bar_empty + 8 * cur.slot);
                cur.next();
            }
            mbar_wait(bar_ok, 0);
            uint32_t* dst = g_gp + f * (NB * DM) + 2 * t * DM + warp * 128 + g;
#pragma unroll
            for (int i = 0; i < 8; i++) {
                st_rlx(dst + 16 * i, nz(__float_as_uint(acc[i][0])));
                st_rlx(dst + 16 * i + DM, nz(__float_as_uint(acc[i][1])));
                st_rlx(dst + 16 * i + 8, nz(__float_as_uint(acc[i][2])));
                st_rlx(dst + 16 * i + 8 + DM, nz(__float_as_uint(acc[i][3])));
            }
            if (tid == 0) STAMP(7);
        }
    }
}

typedef CUresult (*EncodeTiledFn)(CUtensorMap*, CUtensorMapDataType, cuuint32_t, void*, const cuuint64_t*, const cuuint64_t*,
                                  const cuuint32_t*, const cuuint32_t*, CUtensorMapInterleave, CUtensorMapSwizzle,
                                  CUtensorMapL2promotion, CUtensorMapFloatOOBfill);

void encode(EncodeTiledFn fn, CUtensorMap* m, const void* ptr, int rank, const cuuint64_t* dims, const cuuint64_t* strides,
            const cuuint32_t* box, CUtensorMapSwizzle sw, CUtensorMapL2promotion promo) {
    const cuuint32_t es[5] = {1, 1, 1, 1, 1};
    fn(m, CU_TENSOR_MAP_DATA_TYPE_BFLOAT16, rank, const_cast<void*>(ptr), dims, strides, box, es,
       CU_TENSOR_MAP_INTERLEAVE_NONE, sw, promo, CU_TENSOR_MAP_FLOAT_OOB_FILL_NONE);
}

}

extern "C" void kernel_launch(void* const* d_in, const int* in_sizes, int n_in, void* d_out, int out_size) {
    (void)in_sizes; (void)n_in; (void)out_size;
    const __nv_bfloat16* x = (const __nv_bfloat16*)d_in[0];
    const void* kc = d_in[1];
    const void* vc = d_in[2];
    const void* wq = d_in[3];
    const void* wo = d_in[4];
    const void* w1 = d_in[6];
    const __nv_bfloat16* b1 = (const __nv_bfloat16*)d_in[7];
    const void* w2 = d_in[8];
    const __nv_bfloat16* b2 = (const __nv_bfloat16*)d_in[9];

    EncodeTiledFn fn = nullptr;
    cudaDriverEntryPointQueryResult qr;
    cudaGetDriverEntryPoint("cuTensorMapEncodeTiled", (void**)&fn, cudaEnableDefault, &qr);
    cudaFuncSetAttribute(fused_decode_kernel, cudaFuncAttributeMaxDynamicSharedMemorySize, SMEM_BYTES);

    CUtensorMap mK, mV, mWq, mWo, mW1, mW2;
    {
        const cuuint64_t d[3] = {64, (cuuint64_t)NB * HKV * SK, 2}, s[2] = {DH * 2, 128};
        const cuuint32_t bx[3] = {64, 64, 2};
        encode(fn, &mK, kc, 3, d, s, bx, CU_TENSOR_MAP_SWIZZLE_128B, CU_TENSOR_MAP_L2_PROMOTION_L2_256B);
        encode(fn, &mV, vc, 3, d, s, bx, CU_TENSOR_MAP_SWIZZLE_128B, CU_TENSOR_MAP_L2_PROMOTION_L2_256B);
    }
    {
        const cuuint64_t d[2] = {HQ * DH, DM}, s[1] = {HQ * DH * 2};
        const cuuint32_t bx[2] = {32, 256};
        encode(fn, &mWq, wq, 2, d, s, bx, CU_TENSOR_MAP_SWIZZLE_64B, CU_TENSOR_MAP_L2_PROMOTION_L2_128B);
    }
    {
        const cuuint64_t d[5] = {64, 2, 8, HQ * DH / 16, 8}, s[4] = {8 * DM * 2, DM * 2, 16 * DM * 2, 128};
        const cuuint32_t bx[5] = {64, 2, 8, 4, 2};
        encode(fn, &mWo, wo, 5, d, s, bx, CU_TENSOR_MAP_SWIZZLE_128B, CU_TENSOR_MAP_L2_PROMOTION_L2_256B);
    }
    {
        const cuuint64_t d[3] = {64, DM, FF / 64}, s[2] = {FF * 2, 128};
        const cuuint32_t bx[3] = {64, 16, 7};
        encode(fn, &mW1, w1, 3, d, s, bx, CU_TENSOR_MAP_SWIZZLE_128B, CU_TENSOR_MAP_L2_PROMOTION_L2_128B);
    }
    {
        const cuuint64_t d[3] = {64, FF, DM / 64}, s[2] = {DM * 2, 128};
        const cuuint32_t bx[3] = {64, 16, 8};
        encode(fn, &mW2, w2, 3, d, s, bx, CU_TENSOR_MAP_SWIZZLE_128B, CU_TENSOR_MAP_L2_PROMOTION_L2_256B);
    }
    fused_decode_kernel<<<N_CTA, THREADS, SMEM_BYTES>>>(mK, mV, mWq, mWo, mW1, mW2, x, b1, b2, (__nv_bfloat16*)d_out);
}
```

```cpp
#include <cuda_runtime.h>
#include <cuda_bf16.h>
#include <cuda.h>
#include <stdint.h>

namespace {

constexpr int NB = 8, DM = 512, HQ = 32, HKV = 8, SK = 4096, DH = 128, FF = 1792;
constexpr int N_ATT = 128, N_FFN = 4, N_CTA = N_ATT + N_FFN;
constexpr int THREADS = 192;
#define STAGES_ 13
#define D_START_ 2
#define TAU_ 655
#define PACE_OFF_ 16
#define STAGGER_ 1
#define FFN_PACE_ 15
#define WO_WAIT_ 6
#define WO_PROMO_ 2
constexpr int WO_WAIT = WO_WAIT_;
#define D_MIN_ 2
constexpr int STAGES = STAGES_, D_START = D_START_, D_MIN = D_MIN_;
constexpr int PACE_OFF = PACE_OFF_, STAGGER = STAGGER_, FFN_PACE = FFN_PACE_;
constexpr int STAGE_BYTES = 16384;
constexpr int KV_TILES = 32;
constexpr int NT_ATT = 2 + 2 * KV_TILES + 2;
constexpr int W1_TILES = 32, W2_TILES = 28, NT_FFN = W1_TILES + W2_TILES;
constexpr int W1_BYTES = 7 * 16 * 128;
constexpr int FS = FF / N_FFN;
constexpr int XN_STRIDE = DM + 8;
constexpr int H_STRIDE = FS + 8;

constexpr int SM_RING = 0;
constexpr int SM_XN = SM_RING + STAGES * STAGE_BYTES;
constexpr int SM_RED = SM_XN + NB * XN_STRIDE * 2;
constexpr int SM_SC = SM_RED + 7424;
constexpr int SM_BAR = SM_SC + 1024;
constexpr int SM_END = SM_BAR + (2 * STAGES + 2) * 8;
constexpr int SMEM_BYTES = SM_END + 128;
static_assert(SMEM_BYTES <= 232448, "smem");
static_assert(SM_SC % 16 == 0 && SM_BAR % 8 == 0, "align");

__device__ uint32_t g_q[HKV * NB * 16 * 16];
__device__ uint32_t g_ml[HQ * NB * 4];
__device__ uint32_t g_o[NB * HQ * 128];
__device__ uint32_t g_s[NB * 16 * HKV * 32];
__device__ uint32_t g_gp[N_FFN * NB * DM];
__device__ unsigned g_ctr;

#define STAMP(k) do {} while (0)

constexpr int SPIN_LIMIT = 1 << 22;

struct Maps { CUtensorMap m[6]; };

__device__ __forceinline__ void mbar_init(uint32_t bar, uint32_t cnt) {
    asm volatile("mbarrier.init.shared::cta.b64 [%0], %1;" ::"r"(bar), "r"(cnt) : "memory");
}
__device__ __forceinline__ void mbar_expect_tx(uint32_t bar, uint32_t bytes) {
    asm volatile("mbarrier.arrive.expect_tx.shared::cta.b64 _, [%0], %1;" ::"r"(bar), "r"(bytes) : "memory");
}
__device__ __forceinline__ void mbar_arrive(uint32_t bar) {
    asm volatile("mbarrier.arrive.shared::cta.b64 _, [%0];" ::"r"(bar) : "memory");
}
__device__ __forceinline__ void mbar_wait(uint32_t bar, uint32_t parity) {
    uint32_t ok;
    int it = 0;
    do {
        asm volatile("{\n.reg .pred p;\nmbarrier.try_wait.parity.shared::cta.b64 p, [%1], %2;\nselp.u32 %0, 1, 0, p;\n}"
                     : "=r"(ok) : "r"(bar), "r"(parity) : "memory");
        if (++it > SPIN_LIMIT) __trap();
    } while (!ok);
}
__device__ __forceinline__ bool mbar_test(uint32_t bar, uint32_t parity) {
    uint32_t ok;
    asm volatile("{\n.reg .pred p;\nmbarrier.test_wait.parity.shared::cta.b64 p, [%1], %2;\nselp.u32 %0, 1, 0, p;\n}"
                 : "=r"(ok) : "r"(bar), "r"(parity) : "memory");
    return ok;
}
__device__ __forceinline__ void tma3d(uint32_t dst, const CUtensorMap* m, uint32_t bar, int c0, int c1, int c2, uint64_t pol) {
    asm volatile("cp.async.bulk.tensor.3d.shared::cluster.global.mbarrier::complete_tx::bytes.L2::cache_hint [%0], [%1, {%3, %4, %5}], [%2], %6;"
                 ::"r"(dst), "l"(m), "r"(bar), "r"(c0), "r"(c1), "r"(c2), "l"(pol) : "memory");
}
__device__ __forceinline__ void tma5d(uint32_t dst, const CUtensorMap* m, uint32_t bar, int c0, int c3, int c4) {
    asm volatile("cp.async.bulk.tensor.5d.shared::cluster.global.mbarrier::complete_tx::bytes [%0], [%1, {%6, %3, %3, %4, %5}], [%2];"
                 ::"r"(dst), "l"(m), "r"(bar), "r"(0), "r"(c3), "r"(c4), "r"(c0) : "memory");
}
__device__ __forceinline__ void ldsm4(uint32_t (&r)[4], uint32_t addr) {
    asm volatile("ldmatrix.sync.aligned.m8n8.x4.shared.b16 {%0, %1, %2, %3}, [%4];"
                 : "=r"(r[0]), "=r"(r[1]), "=r"(r[2]), "=r"(r[3]) : "r"(addr) : "memory");
}
__device__ __forceinline__ void ldsm4t(uint32_t (&r)[4], uint32_t addr) {
    asm volatile("ldmatrix.sync.aligned.m8n8.x4.trans.shared.b16 {%0, %1, %2, %3}, [%4];"
                 : "=r"(r[0]), "=r"(r[1]), "=r"(r[2]), "=r"(r[3]) : "r"(addr) : "memory");
}
__device__ __forceinline__ void mma16816(float (&c)[4], const uint32_t (&a)[4], uint32_t b0, uint32_t b1) {
    asm volatile("mma.sync.aligned.m16n8k16.row.col.f32.bf16.bf16.f32 {%0, %1, %2, %3}, {%4, %5, %6, %7}, {%8, %9}, {%0, %1, %2, %3};"
                 : "+f"(c[0]), "+f"(c[1]), "+f"(c[2]), "+f"(c[3])
                 : "r"(a[0]), "r"(a[1]), "r"(a[2]), "r"(a[3]), "r"(b0), "r"(b1));
}
__device__ __forceinline__ uint32_t movm_t(uint32_t a) {
    uint32_t d;
    asm volatile("movmatrix.sync.aligned.m8n8.trans.b16 %0, %1;" : "=r"(d) : "r"(a));
    return d;
}
__device__ __forceinline__ uint32_t pack_bf16(float lo, float hi) {
    uint32_t d;
    asm("cvt.rn.bf16x2.f32 %0, %1, %2;" : "=r"(d) : "f"(hi), "f"(lo));
    return d;
}
__device__ __forceinline__ float bf_lo(uint32_t v) { return __uint_as_float(v << 16); }
__device__ __forceinline__ float bf_hi(uint32_t v) { return __uint_as_float(v & 0xffff0000u); }
__device__ __forceinline__ float rbf(float x) { return __bfloat162float(__float2bfloat16_rn(x)); }
__device__ __forceinline__ uint32_t max_bf16x2(uint32_t a, uint32_t b) {
    uint32_t d;
    asm("max.bf16x2 %0, %1, %2;" : "=r"(d) : "r"(a), "r"(b));
    return d;
}
__device__ __forceinline__ uint32_t sub_bf16x2(uint32_t a, uint32_t b) {
    uint32_t d;
    asm("sub.rn.bf16x2 %0, %1, %2;" : "=r"(d) : "r"(a), "r"(b));
    return d;
}
__device__ __forceinline__ float ex2(float x) {
    float y;
    asm("ex2.approx.ftz.f32 %0, %1;" : "=f"(y) : "f"(x));
    return y;
}
__device__ __forceinline__ float rcp(float x) {
    float y;
    asm("rcp.approx.f32 %0, %1;" : "=f"(y) : "f"(x));
    return y;
}
__device__ __forceinline__ uint32_t nz(uint32_t w) { return w == 0u ? 0x80000000u : w; }
__device__ __forceinline__ void st_rlx(uint32_t* p, uint32_t v) {
    asm volatile("st.relaxed.gpu.global.u32 [%0], %1;" ::"l"(p), "r"(v) : "memory");
}
__device__ __forceinline__ void st_rlx2(uint32_t* p, uint32_t a, uint32_t b) {
    asm volatile("st.relaxed.gpu.global.v2.u32 [%0], {%1, %2};" ::"l"(p), "r"(a), "r"(b) : "memory");
}
__device__ __forceinline__ void st_rlx4(uint32_t* p, uint32_t a, uint32_t b, uint32_t c, uint32_t d) {
    asm volatile("st.relaxed.gpu.global.v4.u32 [%0], {%1, %2, %3, %4};" ::"l"(p), "r"(a), "r"(b), "r"(c), "r"(d) : "memory");
}
__device__ __forceinline__ void st_rlx_zero4(uint32_t* p) {
    asm volatile("st.relaxed.gpu.global.v4.u32 [%0], {%1, %1, %1, %1};" ::"l"(p), "r"(0) : "memory");
}
__device__ __forceinline__ uint32_t ld_rlx(const uint32_t* p) {
    uint32_t v;
    asm volatile("ld.relaxed.gpu.global.u32 %0, [%1];" : "=r"(v) : "l"(p) : "memory");
    return v;
}
__device__ __forceinline__ uint4 ld_rlx4(const uint32_t* p) {
    uint4 v;
    asm volatile("ld.relaxed.gpu.global.v4.u32 {%0, %1, %2, %3}, [%4];" : "=r"(v.x), "=r"(v.y), "=r"(v.z), "=r"(v.w) : "l"(p) : "memory");
    return v;
}
__device__ __forceinline__ uint32_t min4(const uint4& v) { return min(min(v.x, v.y), min(v.z, v.w)); }
__device__ __forceinline__ bool elect_one() {
    uint32_t p;
    asm volatile("{\n.reg .pred P;\nelect.sync _|P, 0xffffffff;\nselp.u32 %0, 1, 0, P;\n}" : "=r"(p));
    return p;
}
__device__ __forceinline__ uint32_t timer_ns() {
    uint32_t t;
    asm volatile("mov.u32 %0, %%globaltimer_lo;" : "=r"(t));
    return t;
}
__device__ __forceinline__ void bar_compute() { asm volatile("bar.sync 1, 128;" ::: "memory"); }

struct Cursor {
    int slot = 0;
    uint32_t phase = 0;
    __device__ __forceinline__ void next() { if (++slot == STAGES) { slot = 0; phase ^= 1u; } }
};

constexpr float LOG2E = 1.4426950408889634f;

__global__ void __launch_bounds__(THREADS, 1)
fused_decode_kernel(const __grid_constant__ Maps maps, const __nv_bfloat16* __restrict__ x, const __nv_bfloat16* __restrict__ b1,
                    const __nv_bfloat16* __restrict__ b2, __nv_bfloat16* __restrict__ out, const uint32_t tau) {
    extern __shared__ __align__(1024) uint8_t smem_raw[];
    uint32_t sb;
    asm volatile("{\n.reg .u64 a;\ncvta.to.shared.u64 a, %1;\ncvt.u32.u64 %0, a;\n}" : "=r"(sb) : "l"(smem_raw));
    if (sb & 1023u) __trap();
    uint8_t* sp = smem_raw;
    const uint32_t bar_full = sb + SM_BAR, bar_empty = bar_full + 8 * STAGES;
    const uint32_t bar_ok = bar_empty + 8 * STAGES, bar_late = bar_ok + 8;

    const int warp_id = __shfl_sync(0xffffffffu, (int)(threadIdx.x >> 5), 0), lane = threadIdx.x & 31;
    const int cta = blockIdx.x;
    const bool is_att = cta < N_ATT;
    const int bh = cta >> 1, half = cta & 1;
    const int b = bh >> 3, hkv = bh & 7;
    const int j = 2 * b + half;
    const int f = cta - N_ATT;

    if (warp_id == 0) {
        const bool leader = elect_one();
        if (leader) STAMP(0);
        uint64_t pol;
        asm volatile("createpolicy.fractional.L2::evict_first.b64 %0, 1.0;" : "=l"(pol));
        const int row0 = cta * (SK / 2) - 64;
        auto issue = [&](int i, int slot) {
            const uint32_t dst = sb + SM_RING + slot * STAGE_BYTES, bar = bar_full + 8 * slot;
            int mi, c0 = 0, c1, c2 = 0, bytes = STAGE_BYTES;
            if (is_att) {
                mi = i & 1; c1 = row0 + (i >> 1) * 64;
                if (i < 2) { mi = 2; c0 = hkv * 512 + 32 * j; c1 = 256 * i; }
            } else {
                mi = 4; c1 = FS * f + 16 * (i - W1_TILES);
                if (i < W1_TILES) { mi = 3; c1 = 16 * i; c2 = 7 * f; bytes = W1_BYTES; }
            }
            if (leader) {
                mbar_expect_tx(bar, bytes);
                if (i < NT_ATT - 2) tma3d(dst, &maps.m[mi], bar, c0, c1, c2, pol);
                else tma5d(dst, &maps.m[5], bar, 32 * j, 4 * (i - (NT_ATT - 2)), 4 * hkv);
            }
        };
#pragma unroll
        for (int i = 0; i < D_START; i++)
            if (leader) mbar_init(bar_full + 8 * i, 1);
#pragma unroll
        for (int i = 0; i < D_START; i++) {
            issue(i, i);
            if (i == 0 && leader) STAMP(15);
        }
        const uint32_t t0 = timer_ns();
        __syncthreads();
        const int nt = is_att ? NT_ATT : NT_FFN;
        Cursor cur, lag;
        cur.slot = D_START;
        lag.slot = D_START - D_MIN;
        const uint32_t step = is_att ? tau : tau * FFN_PACE / 16;
        uint32_t due = t0 + step * (PACE_OFF + (cta & 15) * STAGGER) / 16;
#pragma unroll 1
        for (int i = D_START; i < nt; i++) {
            if (i >= STAGES) mbar_wait(bar_empty + 8 * cur.slot, cur.phase ^ 1u);
            if (WO_WAIT > 0 && i >= NT_ATT - 2) {
                constexpr int w = NT_ATT - 2 - WO_WAIT;
                mbar_wait(bar_full + 8 * (w % STAGES), (w / STAGES) & 1);
            } else {
                int it = 0;
                while ((int)(timer_ns() - due) < 0 && ++it < 4096) {
                    if (D_MIN > 0 && mbar_test(bar_full + 8 * lag.slot, lag.phase)) break;
                }
            }
            lag.next();
            due += step;
            issue(i, cur.slot);
            cur.next();
        }
        if (leader) STAMP(1);
    } else if (warp_id == 1) {
        if (elect_one()) {
#pragma unroll
            for (int s = D_START; s < STAGES; s++) mbar_init(bar_full + 8 * s, 1);
#pragma unroll
            for (int s = 0; s < STAGES; s++) mbar_init(bar_empty + 8 * s, 4);
            mbar_init(bar_ok, 1);
            mbar_init(bar_late, 1);
            asm volatile("fence.mbarrier_init.release.cluster;" ::: "memory");
        }
        __syncthreads();
        const int fb = cta >> 4, fcb = cta & 15;
        uint32_t* inbox = g_s + cta * (HKV * 32) + lane * 4;
        {
            uint32_t* clr = is_att ? inbox : g_gp + f * (NB * DM) + lane * 4;
            const int n = is_att ? 2 : 32;
#pragma unroll 1
            for (int i = 0; i < n; i++) st_rlx_zero4(clr + i * 128);
            if (is_att) {
                uint32_t* po = g_o + ((b * HQ + 4 * hkv + (lane >> 4)) * 2 + half) * 64 + (lane & 15) * 4;
                st_rlx_zero4(po);
                st_rlx_zero4(po + 256);
                if (lane < 4) st_rlx2(g_ml + ((4 * hkv + lane) * NB + b) * 4 + half * 2, 0u, 0u);
            }
        }
        __syncwarp();
        if (lane == 0) {
            asm volatile("fence.acq_rel.gpu;" ::: "memory");
            atomicInc(&g_ctr, N_CTA - 1);
            int it = 0;
            while (true) {
                __nanosleep(2000);
                unsigned v;
                asm volatile("ld.acquire.gpu.global.u32 %0, [%1];" : "=r"(v) : "l"(&g_ctr) : "memory");
                if (v == 0u) break;
                if (++it > SPIN_LIMIT) __trap();
            }
            mbar_arrive(bar_ok);
        }
        __syncwarp();
        if (is_att) {
            const int col = fcb * 32 + lane;
            const float xv = __bfloat162float(x[fb * DM + col]);
            const float b2v = __bfloat162float(b2[col]);
            uint4 p;
            int it = 0;
            while (true) {
                const uint32_t* src = g_gp + fb * DM + col;
                p.x = ld_rlx(src); p.y = ld_rlx(src + NB * DM); p.z = ld_rlx(src + 2 * NB * DM); p.w = ld_rlx(src + 3 * NB * DM);
                if (__all_sync(0xffffffffu, min4(p) != 0u)) break;
                __nanosleep(1000);
                if (++it > SPIN_LIMIT) __trap();
            }
            float y = rbf((__uint_as_float(p.x) + __uint_as_float(p.y)) + (__uint_as_float(p.z) + __uint_as_float(p.w)));
            y = rbf(y + b2v);
            const float gate = rbf(__fdividef(y, 1.0f + __expf(-y)));
            if (lane == 0) STAMP(8);
            mbar_wait(bar_late, 0);
            uint4 v0 = {}, v1 = {};
            it = 0;
            bool n0 = true, n1 = true;
            do {
                if (n0) v0 = ld_rlx4(inbox);
                if (n1) v1 = ld_rlx4(inbox + 128);
                n0 = min4(v0) == 0u; n1 = min4(v1) == 0u;
                if (++it > SPIN_LIMIT) __trap();
            } while (__any_sync(0xffffffffu, n0 || n1));
            const float s0 = __uint_as_float(v0.x) + __uint_as_float(v1.x), s1 = __uint_as_float(v0.y) + __uint_as_float(v1.y);
            const float s2 = __uint_as_float(v0.z) + __uint_as_float(v1.z), s3 = __uint_as_float(v0.w) + __uint_as_float(v1.w);
            const bool up = lane & 16;
            float k0 = up ? s2 : s0, k1 = up ? s3 : s1;
            k0 += __shfl_xor_sync(0xffffffffu, up ? s0 : s2, 16);
            k1 += __shfl_xor_sync(0xffffffffu, up ? s1 : s3, 16);
            const bool odd = lane & 8;
            float s = odd ? k1 : k0;
            s += __shfl_xor_sync(0xffffffffu, odd ? k0 : k1, 8);
            out[fb * DM + col] = __float2bfloat16_rn(xv + rbf(rbf(s) * gate));
            if (lane == 0) STAMP(9);
        }
    } else {
        const int warp = warp_id - 2, tid = threadIdx.x - 64;
        const int g = lane >> 2, t = lane & 3;
        {
            const int row = tid >> 4, c = (tid & 15) * 8;
            uint4 xv[4];
#pragma unroll
            for (int i = 0; i < 4; i++) xv[i] = __ldg(reinterpret_cast<const uint4*>(x + row * DM + i * 128 + c));
            __syncthreads();
            uint32_t w[16];
#pragma unroll
            for (int i = 0; i < 4; i++) { w[4 * i] = xv[i].x; w[4 * i + 1] = xv[i].y; w[4 * i + 2] = xv[i].z; w[4 * i + 3] = xv[i].w; }
            float s0 = 0.f, s1 = 0.f;
#pragma unroll
            for (int i = 0; i < 16; i++) { s0 += bf_lo(w[i]); s1 += bf_hi(w[i]); }
            s0 += s1;
#pragma unroll
            for (int o = 8; o > 0; o >>= 1) s0 += __shfl_xor_sync(0xffffffffu, s0, o);
            const float mean = s0 * (1.0f / DM);
            s0 = 0.f; s1 = 0.f;
#pragma unroll
            for (int i = 0; i < 16; i++) {
                const float d0 = bf_lo(w[i]) - mean, d1 = bf_hi(w[i]) - mean;
                s0 += d0 * d0; s1 += d1 * d1;
            }
            s0 += s1;
#pragma unroll
            for (int o = 8; o > 0; o >>= 1) s0 += __shfl_xor_sync(0xffffffffu, s0, o);
            const uint32_t mb = pack_bf16(mean, mean);
            float sd;
            asm("sqrt.approx.f32 %0, %1;" : "=f"(sd) : "f"(rbf(rbf(s0 * (1.0f / DM)) + 1e-5f)));
            const float rs = rcp(rbf(sd));
#pragma unroll
            for (int i = 0; i < 16; i++) {
                const uint32_t d = sub_bf16x2(w[i], mb);
                w[i] = pack_bf16(bf_lo(d) * rs, bf_hi(d) * rs);
            }
#pragma unroll
            for (int i = 0; i < 4; i++)
                *reinterpret_cast<uint4*>(sp + SM_XN + (row * XN_STRIDE + i * 128 + c) * 2) =
                    make_uint4(w[4 * i], w[4 * i + 1], w[4 * i + 2], w[4 * i + 3]);
        }
        bar_compute();
        if (tid == 0) STAMP(11);
        const uint32_t* xn32 = reinterpret_cast<const uint32_t*>(sp + SM_XN) + g * (XN_STRIDE / 2) + t;
        const int krow = (lane & 7) + (lane >> 4) * 8;
        const int cbit = (lane >> 3) & 1;
        Cursor cur;

        if (is_att) {
            uint32_t* qword;
            {
                float acc[2][4] = {};
                const int st = warp >> 1;
                mbar_wait(bar_full + 8 * st, 0);
                const uint32_t base = sb + SM_RING + st * STAGE_BYTES + ((warp & 1) * 128 + krow) * 64;
                const int sw = (krow >> 1) & 3;
#pragma unroll
                for (int ks = 0; ks < 8; ks++) {
                    const uint32_t b0 = xn32[warp * 64 + ks * 8], b1r = xn32[warp * 64 + ks * 8 + 4];
#pragma unroll
                    for (int mt = 0; mt < 2; mt++) {
                        uint32_t a[4];
                        ldsm4t(a, base + ks * 1024 + (((2 * mt + cbit) ^ sw) << 4));
                        mma16816(acc[mt], a, b0, b1r);
                    }
                }
                __syncwarp();
                if (lane < 2) mbar_arrive(bar_empty + 8 * lane);
                cur.next(); cur.next();
                float* red = reinterpret_cast<float*>(sp + SM_RED);
#pragma unroll
                for (int mt = 0; mt < 2; mt++) {
                    red[(warp * 8 + 2 * t) * 36 + 16 * mt + g] = acc[mt][0];
                    red[(warp * 8 + 2 * t + 1) * 36 + 16 * mt + g] = acc[mt][1];
                    red[(warp * 8 + 2 * t) * 36 + 16 * mt + g + 8] = acc[mt][2];
                    red[(warp * 8 + 2 * t + 1) * 36 + 16 * mt + g + 8] = acc[mt][3];
                }
                bar_compute();
                const int qb = tid >> 4, pos = tid & 15;
                const int col = 8 * (pos & 3) + 2 * (pos >> 2);
                float s0 = 0.f, s1 = 0.f;
#pragma unroll
                for (int w = 0; w < 4; w++) {
                    const float2 v = *reinterpret_cast<const float2*>(red + (w * 8 + qb) * 36 + col);
                    s0 += v.x; s1 += v.y;
                }
                qword = g_q + ((hkv * NB + qb) * 16 + j) * 16 + pos;
                st_rlx(qword, nz(pack_bf16(s0, s1)));
            }
            if (tid == 0) STAMP(12);
            uint4 qf[4];
            {
                const uint32_t* src = g_q + ((hkv * NB + b) * 16 + 4 * (g & 3)) * 16 + 4 * t;
                int it = 0;
                while (true) {
#pragma unroll
                    for (int i = 0; i < 4; i++) qf[i] = ld_rlx4(src + 16 * i);
                    if (__all_sync(0xffffffffu, min(min(min4(qf[0]), min4(qf[1])), min(min4(qf[2]), min4(qf[3]))) != 0u)) break;
                    if (++it > SPIN_LIMIT) __trap();
                }
            }
            if (tid == 0) STAMP(3);
            float o[2][2][4] = {};
            float m = -INFINITY, l = 0.f;
            uint32_t koff[4], voff[2];
#pragma unroll
            for (int i = 0; i < 4; i++)
                koff[i] = (16 * warp + (lane & 7) + cbit * 8) * 128 + (((2 * i + (lane >> 4)) ^ (lane & 7)) << 4);
#pragma unroll
            for (int mt = 0; mt < 2; mt++)
                voff[mt] = (warp >> 1) * 8192 + krow * 128 + (((4 * (warp & 1) + 2 * mt + cbit) ^ (lane & 7)) << 4);
            uint8_t* sc = sp + SM_SC + (lane & 15) * 32;
#pragma unroll 1
            for (int tile = 0; tile < KV_TILES; tile++) {
                mbar_wait(bar_full + 8 * cur.slot, cur.phase);
                uint32_t base = sb + SM_RING + cur.slot * STAGE_BYTES;
                float sa[4] = {}, sc2[4] = {};
#pragma unroll
                for (int i = 0; i < 2; i++) {
                    uint32_t a0[4], a1[4], a2[4], a3[4];
                    ldsm4(a0, base + koff[2 * i]);
                    ldsm4(a1, base + 8192 + koff[2 * i]);
                    ldsm4(a2, base + koff[2 * i + 1]);
                    ldsm4(a3, base + 8192 + koff[2 * i + 1]);
                    mma16816(sa, a0, qf[i].x, qf[i].y);
                    mma16816(sc2, a1, qf[2 + i].x, qf[2 + i].y);
                    mma16816(sa, a2, qf[i].z, qf[i].w);
                    mma16816(sc2, a3, qf[2 + i].z, qf[2 + i].w);
                }
                __syncwarp();
                if (lane == 0) mbar_arrive(bar_empty + 8 * cur.slot);
                cur.next();
                uint32_t s01 = pack_bf16(sa[0] + sc2[0], sa[1] + sc2[1]);
                uint32_t s23 = pack_bf16(sa[2] + sc2[2], sa[3] + sc2[3]);
                const float scale = 0.08838834764831845f;
                s01 = movm_t(pack_bf16(bf_lo(s01) * scale, bf_hi(s01) * scale));
                s23 = movm_t(pack_bf16(bf_lo(s23) * scale, bf_hi(s23) * scale));
                uint8_t* scb = sc + (tile & 1) * 512;
                if (lane < 16) *reinterpret_cast<uint2*>(scb + warp * 8) = make_uint2(s01, s23);
                bar_compute();
                const uint4 u0 = *reinterpret_cast<const uint4*>(scb), u1 = *reinterpret_cast<const uint4*>(scb + 16);
                uint32_t p[8] = {u0.x, u0.y, u0.z, u0.w, u1.x, u1.y, u1.z, u1.w};
                const uint32_t mx2 = max_bf16x2(max_bf16x2(max_bf16x2(p[0], p[1]), max_bf16x2(p[2], p[3])),
                                                max_bf16x2(max_bf16x2(p[4], p[5]), max_bf16x2(p[6], p[7])));
                float mx = fmaxf(fmaxf(bf_lo(mx2), bf_hi(mx2)), m);
                mx = fmaxf(mx, __shfl_xor_sync(0xffffffffu, mx, 1));
                mx = fmaxf(mx, __shfl_xor_sync(0xffffffffu, mx, 2));
                const float alpha = ex2((m - mx) * LOG2E);
                m = mx;
                const float a0 = __shfl_sync(0xffffffffu, alpha, (t & 1) * 8), a1 = __shfl_sync(0xffffffffu, alpha, (t & 1) * 8 + 4);
                float ls0 = 0.f, ls1 = 0.f;
#pragma unroll
                for (int i = 0; i < 8; i++) {
                    const float e0 = ex2((bf_lo(p[i]) - mx) * LOG2E), e1 = ex2((bf_hi(p[i]) - mx) * LOG2E);
                    ls0 += e0; ls1 += e1;
                    p[i] = pack_bf16(e0, e1);
                }
                l = l * alpha + (ls0 + ls1);
#pragma unroll
                for (int c = 0; c < 2; c++)
#pragma unroll
                    for (int mt = 0; mt < 2; mt++) { o[c][mt][0] *= a0; o[c][mt][1] *= a1; o[c][mt][2] *= a0; o[c][mt][3] *= a1; }
                if (tile == KV_TILES - 1) {
                    mbar_wait(bar_ok, 0);
                    l += __shfl_xor_sync(0xffffffffu, l, 1);
                    l += __shfl_xor_sync(0xffffffffu, l, 2);
                    if (t == 0 && g == warp)
                        st_rlx2(g_ml + ((4 * hkv + g) * NB + b) * 4 + half * 2, nz(__float_as_uint(m)), nz(__float_as_uint(l)));
                }
                mbar_wait(bar_full + 8 * cur.slot, cur.phase);
                base = sb + SM_RING + cur.slot * STAGE_BYTES;
#pragma unroll
                for (int ks = 0; ks < 4; ks++) {
                    uint32_t a0r[4], a1r[4];
                    ldsm4t(a0r, base + ks * 2048 + voff[0]);
                    ldsm4t(a1r, base + ks * 2048 + voff[1]);
                    mma16816(o[ks & 1][0], a0r, p[2 * ks], p[2 * ks + 1]);
                    mma16816(o[ks & 1][1], a1r, p[2 * ks], p[2 * ks + 1]);
                }
                __syncwarp();
                if (lane == 0) mbar_arrive(bar_empty + 8 * cur.slot);
                cur.next();
            }
            {
                const bool hi = t >= 2;
                float c[4];
#pragma unroll
                for (int i = 0; i < 4; i++) c[i] = hi ? o[0][1][i] + o[1][1][i] : o[0][0][i] + o[1][0][i];
                uint32_t* dst = g_o + ((b * HQ + 4 * hkv + 2 * (t & 1)) * 2 + half) * 64 + 16 * warp + 4 * (g & 3) + (t & 2) + (g >> 2);
                st_rlx(dst, nz(pack_bf16(c[0], c[2])));
                st_rlx(dst + 128, nz(pack_bf16(c[1], c[3])));
            }
            if (tid == 0) STAMP(5);
            {
                const uint32_t* src = g_o + (g * HQ + 4 * hkv + warp) * 128 + 4 * t;
                const uint32_t* srcml = g_ml + ((4 * hkv + warp) * NB + g) * 4;
                uint32_t wf[8][2][4];
                const uint32_t woff = warp * 4096 + krow * 64;
                const uint32_t wb0 = sb + SM_RING + cur.slot * STAGE_BYTES + woff, wbar0 = bar_full + 8 * cur.slot, wph0 = cur.phase;
                cur.next();
                const uint32_t wb1 = sb + SM_RING + cur.slot * STAGE_BYTES + woff, wbar1 = bar_full + 8 * cur.slot, wph1 = cur.phase;
                const int sw = (krow >> 1) & 3;
                auto load_w = [&](int s) {
#pragma unroll
                    for (int a = 0; a < 4; a++)
#pragma unroll
                        for (int mt = 0; mt < 2; mt++) ldsm4t(wf[4 * s + a][mt], (s ? wb1 : wb0) + a * 1024 + (((2 * mt + cbit) ^ sw) << 4));
                };
                uint4 ml = {}, va[4] = {}, vb[4] = {};
                bool first = true, need_ml = true, need_a = true, need_b = true, got_w = false;
                int it = 0;
                do {
                    if (need_a && (first || ml.x != 0u)) {
#pragma unroll
                        for (int i = 0; i < 4; i++) va[i] = ld_rlx4(src + 16 * i);
                    }
                    if (need_b && (first || ml.z != 0u)) {
#pragma unroll
                        for (int i = 0; i < 4; i++) vb[i] = ld_rlx4(src + 64 + 16 * i);
                    }
                    if (need_ml) ml = ld_rlx4(srcml);
                    first = false;
                    if (!got_w && mbar_test(wbar0, wph0) && mbar_test(wbar1, wph1)) { load_w(0); load_w(1); got_w = true; }
                    need_ml = min4(ml) == 0u;
                    need_a = min(min(min4(va[0]), min4(va[1])), min(min4(va[2]), min4(va[3]))) == 0u;
                    need_b = min(min(min4(vb[0]), min4(vb[1])), min(min4(vb[2]), min4(vb[3]))) == 0u;
                    if (++it > SPIN_LIMIT) __trap();
                } while (__any_sync(0xffffffffu, need_ml || need_a || need_b));
                if (tid == 0) mbar_arrive(bar_late);
                {
                    const float ma = __uint_as_float(ml.x), mb = __uint_as_float(ml.z), mm = fmaxf(ma, mb);
                    const float ea = ex2((ma - mm) * LOG2E), eb = ex2((mb - mm) * LOG2E);
                    const float inv = rcp(ea * __uint_as_float(ml.y) + eb * __uint_as_float(ml.w));
                    const float fa = ea * inv, fb = eb * inv;
#pragma unroll
                    for (int i = 0; i < 4; i++) {
                        va[i].x = pack_bf16(fa * bf_lo(va[i].x) + fb * bf_lo(vb[i].x), fa * bf_hi(va[i].x) + fb * bf_hi(vb[i].x));
                        va[i].y = pack_bf16(fa * bf_lo(va[i].y) + fb * bf_lo(vb[i].y), fa * bf_hi(va[i].y) + fb * bf_hi(vb[i].y));
                        va[i].z = pack_bf16(fa * bf_lo(va[i].z) + fb * bf_lo(vb[i].z), fa * bf_hi(va[i].z) + fb * bf_hi(vb[i].z));
                        va[i].w = pack_bf16(fa * bf_lo(va[i].w) + fb * bf_lo(vb[i].w), fa * bf_hi(va[i].w) + fb * bf_hi(vb[i].w));
                    }
                }
                if (tid == 0) STAMP(14);
                if (!got_w) { mbar_wait(wbar0, wph0); load_w(0); mbar_wait(wbar1, wph1); load_w(1); }
                if (tid == 0) STAMP(6);
                float acc[2][2][4] = {};
#pragma unroll
                for (int i = 0; i < 4; i++)
#pragma unroll
                    for (int mt = 0; mt < 2; mt++) {
                        mma16816(acc[0][mt], wf[2 * i][mt], va[i].x, va[i].y);
                        mma16816(acc[1][mt], wf[2 * i + 1][mt], va[i].z, va[i].w);
                    }
#pragma unroll
                for (int c = 0; c < 2; c++)
                    *reinterpret_cast<float4*>(sp + SM_RED + warp * 1024 + (2 * t + c) * 128 + ((g + 2 * t) & 7) * 16) =
                        make_float4(acc[0][0][c] + acc[1][0][c], acc[0][0][c + 2] + acc[1][0][c + 2],
                                    acc[0][1][c] + acc[1][1][c], acc[0][1][c + 2] + acc[1][1][c + 2]);
                bar_compute();
                float2 r[4];
#pragma unroll
                for (int w = 0; w < 4; w++) r[w] = *reinterpret_cast<const float2*>(sp + SM_RED + w * 1024 + tid * 8);
                const int ob = tid >> 4;
                st_rlx2(g_s + ((ob * 16 + j) * HKV + hkv) * 32 + 4 * (((tid >> 1) - (ob & 6)) & 7) + 2 * (tid & 1),
                        nz(__float_as_uint((r[0].x + r[1].x) + (r[2].x + r[3].x))), nz(__float_as_uint((r[0].y + r[1].y) + (r[2].y + r[3].y))));
                st_rlx(qword, 0u);
                if (tid == 0) STAMP(7);
            }
        } else {
            float acc[8][4] = {};
            if (tid < FS / 8) *reinterpret_cast<uint4*>(sp + SM_SC + tid * 16) = __ldg(reinterpret_cast<const uint4*>(b1 + FS * f) + tid);
            const __nv_bfloat16* b1s = reinterpret_cast<const __nv_bfloat16*>(sp + SM_SC);
            const uint32_t* bsrc = xn32;
            int mt0 = warp * 7;
#pragma unroll 1
            for (int kt = 0; kt < NT_FFN; kt++) {
                if (kt == W1_TILES) {
                    __nv_bfloat16* hs = reinterpret_cast<__nv_bfloat16*>(sp + SM_RED);
#pragma unroll
                    for (int i = 0; i < 7; i++)
#pragma unroll
                        for (int c = 0; c < 4; c++)
                            hs[(2 * t + (c & 1)) * H_STRIDE + (mt0 + i) * 16 + g + (c >> 1) * 8] = __float2bfloat16_rn(acc[i][c]);
                    bar_compute();
#pragma unroll 1
                    for (int e = tid; e < NB * FS; e += 128) {
                        const int r = e / FS, u = e - r * FS;
                        const float hv = rbf(__bfloat162float(hs[r * H_STRIDE + u]) + __bfloat162float(b1s[u]));
                        const float inner = 0.7978845608028654f * (hv + 0.044715f * hv * hv * hv);
                        hs[r * H_STRIDE + u] = __float2bfloat16_rn(0.5f * hv * (1.0f + tanhf(inner)));
                    }
                    bar_compute();
#pragma unroll
                    for (int i = 0; i < 8; i++) { acc[i][0] = 0.f; acc[i][1] = 0.f; acc[i][2] = 0.f; acc[i][3] = 0.f; }
                    bsrc = reinterpret_cast<const uint32_t*>(sp + SM_RED) + g * (H_STRIDE / 2) + t;
                    mt0 = warp * 8;
                }
                const uint32_t b0 = bsrc[0], b1r = bsrc[4];
                bsrc += 8;
                mbar_wait(bar_full + 8 * cur.slot, cur.phase);
                const uint32_t base = sb + SM_RING + cur.slot * STAGE_BYTES + krow * 128;
#pragma unroll
                for (int i = 0; i < 8; i++) {
                    if (i < 7 || kt >= W1_TILES) {
                        const int mt = mt0 + i;
                        uint32_t a[4];
                        ldsm4t(a, base + (mt >> 2) * 2048 + (((2 * (mt & 3) + cbit) ^ (lane & 7)) << 4));
                        mma16816(acc[i], a, b0, b1r);
                    }
                }
                __syncwarp();
                if (lane == 0) mbar_arrive(bar_empty + 8 * cur.slot);
                cur.next();
            }
            mbar_wait(bar_ok, 0);
            uint32_t* dst = g_gp + f * (NB * DM) + 2 * t * DM + warp * 128 + g;
#pragma unroll
            for (int i = 0; i < 8; i++)
#pragma unroll
                for (int c = 0; c < 4; c++) st_rlx(dst + 16 * i + (c >> 1) * 8 + (c & 1) * DM, nz(__float_as_uint(acc[i][c])));
            if (tid == 0) STAMP(7);
        }
    }
}

typedef CUresult (*EncodeTiledFn)(CUtensorMap*, CUtensorMapDataType, cuuint32_t, void*, const cuuint64_t*, const cuuint64_t*,
                                  const cuuint32_t*, const cuuint32_t*, CUtensorMapInterleave, CUtensorMapSwizzle,
                                  CUtensorMapL2promotion, CUtensorMapFloatOOBfill);

void encode(EncodeTiledFn fn, CUtensorMap* m, const void* ptr, int rank, const cuuint64_t* dims, const cuuint64_t* strides,
            const cuuint32_t* box, CUtensorMapSwizzle sw, CUtensorMapL2promotion promo) {
    const cuuint32_t es[5] = {1, 1, 1, 1, 1};
    fn(m, CU_TENSOR_MAP_DATA_TYPE_BFLOAT16, rank, const_cast<void*>(ptr), dims, strides, box, es,
       CU_TENSOR_MAP_INTERLEAVE_NONE, sw, promo, CU_TENSOR_MAP_FLOAT_OOB_FILL_NONE);
}

}

extern "C" void kernel_launch(void* const* d_in, const int* in_sizes, int n_in, void* d_out, int out_size) {
    (void)in_sizes; (void)n_in; (void)out_size;
    const __nv_bfloat16* x = (const __nv_bfloat16*)d_in[0];
    const void* kc = d_in[1];
    const void* vc = d_in[2];
    const void* wq = d_in[3];
    const void* wo = d_in[4];
    const void* w1 = d_in[6];
    const __nv_bfloat16* b1 = (const __nv_bfloat16*)d_in[7];
    const void* w2 = d_in[8];
    const __nv_bfloat16* b2 = (const __nv_bfloat16*)d_in[9];

    EncodeTiledFn fn = nullptr;
    cudaDriverEntryPointQueryResult qr;
    cudaGetDriverEntryPoint("cuTensorMapEncodeTiled", (void**)&fn, cudaEnableDefault, &qr);
    cudaFuncSetAttribute(fused_decode_kernel, cudaFuncAttributeMaxDynamicSharedMemorySize, SMEM_BYTES);

    Maps maps;
    {
        const cuuint64_t d[3] = {64, (cuuint64_t)NB * HKV * SK, 2}, s[2] = {DH * 2, 128};
        const cuuint32_t bx[3] = {64, 64, 2};
        encode(fn, &maps.m[0], kc, 3, d, s, bx, CU_TENSOR_MAP_SWIZZLE_128B, CU_TENSOR_MAP_L2_PROMOTION_L2_256B);
        encode(fn, &maps.m[1], vc, 3, d, s, bx, CU_TENSOR_MAP_SWIZZLE_128B, CU_TENSOR_MAP_L2_PROMOTION_L2_256B);
    }
    {
        const cuuint64_t d[3] = {HQ * DH, DM, 1}, s[2] = {HQ * DH * 2, (cuuint64_t)HQ * DH * 2 * DM};
        const cuuint32_t bx[3] = {32, 256, 1};
        encode(fn, &maps.m[2], wq, 3, d, s, bx, CU_TENSOR_MAP_SWIZZLE_64B, CU_TENSOR_MAP_L2_PROMOTION_L2_128B);
    }
    {
        const cuuint64_t d[3] = {64, DM, FF / 64}, s[2] = {FF * 2, 128};
        const cuuint32_t bx[3] = {64, 16, 7};
        encode(fn, &maps.m[3], w1, 3, d, s, bx, CU_TENSOR_MAP_SWIZZLE_128B, CU_TENSOR_MAP_L2_PROMOTION_L2_128B);
    }
    {
        const cuuint64_t d[3] = {64, FF, DM / 64}, s[2] = {DM * 2, 128};
        const cuuint32_t bx[3] = {64, 16, 8};
        encode(fn, &maps.m[4], w2, 3, d, s, bx, CU_TENSOR_MAP_SWIZZLE_128B, CU_TENSOR_MAP_L2_PROMOTION_L2_256B);
    }
    {
        const cuuint64_t d[5] = {DM, 2, 8, 8, HQ}, s[4] = {8 * DM * 2, DM * 2, 16 * DM * 2, DH * DM * 2};
        const cuuint32_t bx[5] = {32, 2, 8, 4, 4};
        encode(fn, &maps.m[5], wo, 5, d, s, bx, CU_TENSOR_MAP_SWIZZLE_64B, (CUtensorMapL2promotion)WO_PROMO_);
    }
    fused_decode_kernel<<<N_CTA, THREADS, SMEM_BYTES>>>(maps, x, b1, b2, (__nv_bfloat16*)d_out, TAU_);
}
```

```cpp
#include <cuda_runtime.h>
#include <cuda_bf16.h>
#include <cuda.h>
#include <stdint.h>

namespace {

constexpr int NB = 8, DM = 512, HQ = 32, HKV = 8, SK = 4096, DH = 128, FF = 1792;
constexpr int N_ATT = 64, N_FFN = 7, N_CTA = 72;
constexpr int THREADS = 352;
#define D_START_ 4
#define D_MIN_ 4
#define TAU_ 327
#define PACE_OFF_ 40
#define PROD_SLEEP_ 0
#define SLIP_ 4
#define D_HI_ 7
constexpr int SLIP = SLIP_, D_HI = D_HI_;
#define STAGGER_ 1
#define FFN_PACE_ 56
constexpr int STAGES = 12, D_START = D_START_, D_MIN = D_MIN_;
constexpr int PACE_OFF = PACE_OFF_, STAGGER = STAGGER_, FFN_PACE = FFN_PACE_;
constexpr int STAGE_BYTES = 16384;
constexpr int KV_TILES = 64;
constexpr int NT_ATT = 4 + 2 * KV_TILES + 4;
constexpr int FS = 256;
constexpr int NT_FFN = 32;
constexpr int XN_STRIDE = DM + 8;
constexpr int H_STRIDE = FS + 8;

constexpr int SM_RING = 0;
constexpr int SM_XN = SM_RING + STAGES * STAGE_BYTES;
constexpr int SM_QIN = SM_XN + NB * XN_STRIDE * 2;
constexpr int SM_ML = SM_QIN + 1024;
constexpr int SM_H = SM_ML + 256;
constexpr int SM_BAR = SM_H + NB * H_STRIDE * 2;
constexpr int SM_END = SM_BAR + (2 * STAGES + 4) * 8;
constexpr int SMEM_BYTES = SM_END + 128;
static_assert(SMEM_BYTES <= 232448, "smem");
static_assert(SM_QIN % 16 == 0 && SM_BAR % 8 == 0, "align");

__device__ uint32_t g_s[N_ATT * 2 * HKV * 32];
__device__ uint32_t g_gp[N_FFN * NB * DM];
__device__ unsigned g_ctr;

#define STAMP(k) do {} while (0)

constexpr int SPIN_LIMIT = 1 << 22;

struct Maps { CUtensorMap m[6]; };

__device__ __forceinline__ void mbar_init(uint32_t bar, uint32_t cnt) {
    asm volatile("mbarrier.init.shared::cta.b64 [%0], %1;" ::"r"(bar), "r"(cnt) : "memory");
}
__device__ __forceinline__ void mbar_expect_tx(uint32_t bar, uint32_t bytes) {
    asm volatile("mbarrier.arrive.expect_tx.shared::cta.b64 _, [%0], %1;" ::"r"(bar), "r"(bytes) : "memory");
}
__device__ __forceinline__ void mbar_arrive(uint32_t bar) {
    asm volatile("mbarrier.arrive.shared::cta.b64 _, [%0];" ::"r"(bar) : "memory");
}
__device__ __forceinline__ void mbar_wait(uint32_t bar, uint32_t parity) {
    uint32_t ok;
    int it = 0;
    do {
        asm volatile("{\n.reg .pred p;\nmbarrier.try_wait.parity.shared::cta.b64 p, [%1], %2;\nselp.u32 %0, 1, 0, p;\n}"
                     : "=r"(ok) : "r"(bar), "r"(parity) : "memory");
        if (++it > SPIN_LIMIT) __trap();
    } while (!ok);
}
__device__ __forceinline__ void mbar_wait_cluster(uint32_t bar, uint32_t parity) {
    uint32_t ok;
    int it = 0;
    do {
        asm volatile("{\n.reg .pred p;\nmbarrier.try_wait.parity.relaxed.cluster.shared::cta.b64 p, [%1], %2;\nselp.u32 %0, 1, 0, p;\n}"
                     : "=r"(ok) : "r"(bar), "r"(parity) : "memory");
        if (++it > SPIN_LIMIT) __trap();
    } while (!ok);
    asm volatile("fence.acquire.sync_restrict::shared::cluster.cluster;" ::: "memory");
}
__device__ __forceinline__ bool mbar_test(uint32_t bar, uint32_t parity) {
    uint32_t ok;
    asm volatile("{\n.reg .pred p;\nmbarrier.test_wait.parity.shared::cta.b64 p, [%1], %2;\nselp.u32 %0, 1, 0, p;\n}"
                 : "=r"(ok) : "r"(bar), "r"(parity) : "memory");
    return ok;
}
__device__ __forceinline__ bool mbar_try_for(uint32_t bar, uint32_t parity, uint32_t ns) {
    uint32_t ok;
    asm volatile("{\n.reg .pred p;\nmbarrier.try_wait.parity.shared::cta.b64 p, [%1], %2, %3;\nselp.u32 %0, 1, 0, p;\n}"
                 : "=r"(ok) : "r"(bar), "r"(parity), "r"(ns) : "memory");
    return ok;
}
__device__ __forceinline__ void tma3d(uint32_t dst, const CUtensorMap* m, uint32_t bar, int c1, int c2, uint64_t pol) {
    asm volatile("cp.async.bulk.tensor.3d.shared::cluster.global.mbarrier::complete_tx::bytes.L2::cache_hint [%0], [%1, {%3, %4, %5}], [%2], %6;"
                 ::"r"(dst), "l"(m), "r"(bar), "r"(0), "r"(c1), "r"(c2), "l"(pol) : "memory");
}
__device__ __forceinline__ uint32_t mapa(uint32_t addr, uint32_t rank) {
    uint32_t r;
    asm("mapa.shared::cluster.u32 %0, %1, %2;" : "=r"(r) : "r"(addr), "r"(rank));
    return r;
}
__device__ __forceinline__ void st_async2(uint32_t addr, uint32_t a, uint32_t b, uint32_t bar) {
    asm volatile("st.async.shared::cluster.mbarrier::complete_tx::bytes.v2.b32 [%0], {%1, %2}, [%3];"
                 ::"r"(addr), "r"(a), "r"(b), "r"(bar) : "memory");
}
__device__ __forceinline__ void st_async4(uint32_t addr, const uint4& v, uint32_t bar) {
    asm volatile("st.async.shared::cluster.mbarrier::complete_tx::bytes.v4.b32 [%0], {%1, %2, %3, %4}, [%5];"
                 ::"r"(addr), "r"(v.x), "r"(v.y), "r"(v.z), "r"(v.w), "r"(bar) : "memory");
}
__device__ __forceinline__ void cluster_arrive() { asm volatile("barrier.cluster.arrive.relaxed.aligned;" ::: "memory"); }
__device__ __forceinline__ void cluster_wait() { asm volatile("barrier.cluster.wait.aligned;" ::: "memory"); }
__device__ __forceinline__ void sts32(uint32_t addr, uint32_t v) {
    asm volatile("st.shared.b32 [%0], %1;" ::"r"(addr), "r"(v) : "memory");
}
__device__ __forceinline__ float2 lds64f(uint32_t addr) {
    float2 v;
    asm volatile("ld.shared.v2.f32 {%0, %1}, [%2];" : "=f"(v.x), "=f"(v.y) : "r"(addr) : "memory");
    return v;
}
__device__ __forceinline__ uint4 lds128(uint32_t addr) {
    uint4 v;
    asm volatile("ld.shared.v4.b32 {%0, %1, %2, %3}, [%4];" : "=r"(v.x), "=r"(v.y), "=r"(v.z), "=r"(v.w) : "r"(addr) : "memory");
    return v;
}
__device__ __forceinline__ void ldsm4(uint32_t (&r)[4], uint32_t addr) {
    asm volatile("ldmatrix.sync.aligned.m8n8.x4.shared.b16 {%0, %1, %2, %3}, [%4];"
                 : "=r"(r[0]), "=r"(r[1]), "=r"(r[2]), "=r"(r[3]) : "r"(addr) : "memory");
}
__device__ __forceinline__ void ldsm4t(uint32_t (&r)[4], uint32_t addr) {
    asm volatile("ldmatrix.sync.aligned.m8n8.x4.trans.shared.b16 {%0, %1, %2, %3}, [%4];"
                 : "=r"(r[0]), "=r"(r[1]), "=r"(r[2]), "=r"(r[3]) : "r"(addr) : "memory");
}
__device__ __forceinline__ void mma16816(float (&c)[4], const uint32_t (&a)[4], uint32_t b0, uint32_t b1) {
    asm volatile("mma.sync.aligned.m16n8k16.row.col.f32.bf16.bf16.f32 {%0, %1, %2, %3}, {%4, %5, %6, %7}, {%8, %9}, {%0, %1, %2, %3};"
                 : "+f"(c[0]), "+f"(c[1]), "+f"(c[2]), "+f"(c[3])
                 : "r"(a[0]), "r"(a[1]), "r"(a[2]), "r"(a[3]), "r"(b0), "r"(b1));
}
__device__ __forceinline__ uint32_t movm_t(uint32_t a) {
    uint32_t d;
    asm volatile("movmatrix.sync.aligned.m8n8.trans.b16 %0, %1;" : "=r"(d) : "r"(a));
    return d;
}
__device__ __forceinline__ uint32_t pack_bf16(float lo, float hi) {
    uint32_t d;
    asm("cvt.rn.bf16x2.f32 %0, %1, %2;" : "=r"(d) : "f"(hi), "f"(lo));
    return d;
}
__device__ __forceinline__ float bf_lo(uint32_t v) { return __uint_as_float(v << 16); }
__device__ __forceinline__ float bf_hi(uint32_t v) { return __uint_as_float(v & 0xffff0000u); }
__device__ __forceinline__ float rbf(float x) { return __bfloat162float(__float2bfloat16_rn(x)); }
__device__ __forceinline__ uint32_t max_bf16x2(uint32_t a, uint32_t b) {
    uint32_t d;
    asm("max.bf16x2 %0, %1, %2;" : "=r"(d) : "r"(a), "r"(b));
    return d;
}
__device__ __forceinline__ uint32_t sub_bf16x2(uint32_t a, uint32_t b) {
    uint32_t d;
    asm("sub.rn.bf16x2 %0, %1, %2;" : "=r"(d) : "r"(a), "r"(b));
    return d;
}
__device__ __forceinline__ float ex2(float x) {
    float y;
    asm("ex2.approx.ftz.f32 %0, %1;" : "=f"(y) : "f"(x));
    return y;
}
__device__ __forceinline__ float rcp(float x) {
    float y;
    asm("rcp.approx.ftz.f32 %0, %1;" : "=f"(y) : "f"(x));
    return y;
}
__device__ __forceinline__ uint32_t nz(float f) { const uint32_t w = __float_as_uint(f); return w == 0u ? 0x80000000u : w; }
__device__ __forceinline__ void st_rlx(uint32_t* p, uint32_t v) {
    asm volatile("st.relaxed.gpu.global.u32 [%0], %1;" ::"l"(p), "r"(v) : "memory");
}
__device__ __forceinline__ void st_rlx2(uint32_t* p, uint32_t a, uint32_t b) {
    asm volatile("st.relaxed.gpu.global.v2.u32 [%0], {%1, %2};" ::"l"(p), "r"(a), "r"(b) : "memory");
}
__device__ __forceinline__ void st_rlx_zero4(uint32_t* p) {
    asm volatile("st.relaxed.gpu.global.v4.u32 [%0], {%1, %1, %1, %1};" ::"l"(p), "r"(0) : "memory");
}
__device__ __forceinline__ uint32_t ld_rlx(const uint32_t* p) {
    uint32_t v;
    asm volatile("ld.relaxed.gpu.global.u32 %0, [%1];" : "=r"(v) : "l"(p) : "memory");
    return v;
}
__device__ __forceinline__ uint4 ld_rlx4(const uint32_t* p) {
    uint4 v;
    asm volatile("ld.relaxed.gpu.global.v4.u32 {%0, %1, %2, %3}, [%4];" : "=r"(v.x), "=r"(v.y), "=r"(v.z), "=r"(v.w) : "l"(p) : "memory");
    return v;
}
__device__ __forceinline__ uint32_t min4(const uint4& v) { return min(min(v.x, v.y), min(v.z, v.w)); }
__device__ __forceinline__ bool elect_one() {
    uint32_t p;
    asm volatile("{\n.reg .pred P;\nelect.sync _|P, 0xffffffff;\nselp.u32 %0, 1, 0, P;\n}" : "=r"(p));
    return p;
}
__device__ __forceinline__ uint32_t timer_ns() {
    uint32_t t;
    asm volatile("mov.u32 %0, %%globaltimer_lo;" : "=r"(t));
    return t;
}
__device__ __forceinline__ void bar_compute() { asm volatile("bar.sync 1, 256;" ::: "memory"); }

struct Cursor {
    int slot = 0;
    uint32_t phase = 0;
    __device__ __forceinline__ void adv(int n) { slot += n; if (slot >= STAGES) { slot -= STAGES; phase ^= 1u; } }
};

constexpr float LOG2E = 1.4426950408889634f;

template <bool FIRST>
__device__ __forceinline__ void project(float (&r)[4], uint32_t wbase, uint32_t abase, uint32_t bar_full, uint32_t bar_act, int lane) {
    constexpr uint32_t phase = FIRST ? 0 : ((NT_ATT - 4) / STAGES) & 1;
    static_assert((NT_ATT - 4) % STAGES == 0, "wo must start in slot 0");
    uint32_t a[4][8][4];
    float acc[4][4] = {};
#pragma unroll
    for (int s = 0; s < 3; s++) {
        mbar_wait(bar_full + 8 * s, phase);
#pragma unroll
        for (int ks = 0; ks < 8; ks++) ldsm4t(a[s][ks], wbase + s * STAGE_BYTES + ks * 2048);
    }
    if (!FIRST) {
        mbar_wait_cluster(bar_act, 0);
        cluster_arrive();
    }
    uint32_t bl[4][4];
#pragma unroll
    for (int s = 0; s < 3; s++)
#pragma unroll
        for (int i = 0; i < 4; i++) {
            uint32_t bf[4];
            ldsm4(bf, abase + s * 256 + i * 64);
            mma16816(acc[(2 * i) & 3], a[s][2 * i], bf[0], bf[1]);
            mma16816(acc[(2 * i + 1) & 3], a[s][2 * i + 1], bf[2], bf[3]);
        }
#pragma unroll
    for (int i = 0; i < 4; i++) ldsm4(bl[i], abase + 768 + i * 64);
    mbar_wait(bar_full + 24, phase);
#pragma unroll
    for (int ks = 0; ks < 8; ks++) ldsm4t(a[3][ks], wbase + 3 * STAGE_BYTES + ks * 2048);
#pragma unroll
    for (int ks = 0; ks < 8; ks++) mma16816(acc[ks & 3], a[3][ks], bl[ks >> 1][2 * (ks & 1)], bl[ks >> 1][2 * (ks & 1) + 1]);
    if (FIRST) {
        __syncwarp();
        if (lane < 4) mbar_arrive(bar_full + 8 * (STAGES + lane));
    }
#pragma unroll
    for (int i = 0; i < 4; i++) r[i] = (acc[0][i] + acc[1][i]) + (acc[2][i] + acc[3][i]);
}

__global__ void __cluster_dims__(8, 1, 1) __launch_bounds__(THREADS, 1)
fused_decode_kernel(const __grid_constant__ Maps maps, const __nv_bfloat16* __restrict__ x, const __nv_bfloat16* __restrict__ b1,
                    const __nv_bfloat16* __restrict__ b2, __nv_bfloat16* __restrict__ out, uint32_t* mail_s, uint32_t* mail_g, const uint32_t tau) {
    extern __shared__ __align__(1024) uint8_t smem_raw[];
    uint32_t sb;
    asm volatile("{\n.reg .u64 a;\ncvta.to.shared.u64 a, %1;\ncvt.u32.u64 %0, a;\n}" : "=r"(sb) : "l"(smem_raw));
    uint8_t* sp = smem_raw;
    const uint32_t bar_full = sb + SM_BAR, bar_empty = bar_full + 8 * STAGES;
    const uint32_t bar_ok = bar_empty + 8 * STAGES, bar_q = bar_ok + 8, bar_o = bar_q + 8;

    const int warp_id = __shfl_sync(0xffffffffu, (int)(threadIdx.x >> 5), 0), lane = threadIdx.x & 31;
    const int cta = blockIdx.x;
    const bool is_att = cta < N_ATT;
    const int hkv = cta >> 3, rank = cta & 7;

    if (warp_id == 0) {
        const bool leader = elect_one();
        if (leader) STAMP(0);
        uint64_t pol;
        asm volatile("createpolicy.fractional.L2::evict_first.b64 %0, 1.0;" : "=l"(pol));
        const int nt = is_att ? NT_ATT : rank < N_FFN ? NT_FFN : 0;
        const int row0 = (rank * HKV + hkv) * SK - 128;
        auto issue = [&](int i, int slot) {
            const uint32_t dst = sb + SM_RING + slot * STAGE_BYTES, bar = bar_full + 8 * slot;
            int mi, c1, c2 = 0;
            if (is_att) {
                mi = (i >> 1) & 1; c1 = row0 + (i >> 2) * 128 + (i & 1) * 64;
                if (i < 4) { mi = 2; c1 = 128 * i; c2 = cta; }
                if (i >= NT_ATT - 4) { mi = 3; c1 = 512 * hkv + 128 * (i - (NT_ATT - 4)); c2 = rank; }
            } else {
                mi = 5; c1 = FS * rank + 16 * (i - 16);
                if (i < 16) { mi = 4; c1 = 32 * i; c2 = 4 * rank; }
            }
            if (leader) {
                mbar_expect_tx(bar, STAGE_BYTES);
                tma3d(dst, &maps.m[mi], bar, c1, c2, pol);
            }
        };
#pragma unroll
        for (int i = 0; i < D_START; i++)
            if (leader) mbar_init(bar_full + 8 * i, 1);
        if (nt > 0) {
#pragma unroll
            for (int i = 0; i < D_START; i++) {
                issue(i, i);
            }
        }
        const uint32_t t0 = timer_ns();
        __syncthreads();
        if (is_att) cluster_arrive();
        Cursor cur, lag, hi;
        cur.slot = D_START;
        lag.slot = D_START - D_MIN;
        const uint32_t step = is_att ? tau : tau * FFN_PACE / 16;
        uint32_t due = t0 + step * (PACE_OFF + (cta & 15) * STAGGER) / 16;
#pragma unroll 1
        for (int i = D_START; i < nt; i++) {
            if (i >= STAGES) mbar_wait(bar_empty + 8 * cur.slot, cur.phase ^ 1u);
            int it = 0;
            while ((int)(timer_ns() - due) < 0 && ++it < 4096) {
                if (is_att && mbar_test(bar_full + 8 * lag.slot, lag.phase)) break;
            }
            lag.adv(1);
            due += step;
            if (SLIP > 0 && i >= D_HI) {
                if (!mbar_test(bar_full + 8 * hi.slot, hi.phase)) due += step * SLIP / 16;
                hi.adv(1);
            }
            issue(i, cur.slot);
            cur.adv(1);
        }
        if (leader) STAMP(1);
    } else if (warp_id < 3) {
        const int a = warp_id - 1;
        if (a == 0 && elect_one()) {
            if (sb & 1023u) __trap();
#pragma unroll
            for (int s = D_START; s < STAGES; s++) mbar_init(bar_full + 8 * s, 1);
#pragma unroll
            for (int s = 0; s < STAGES; s++) mbar_init(bar_empty + 8 * s, is_att ? 4 : 8);
            mbar_init(bar_ok, 2);
            mbar_init(bar_q, 1);
            mbar_init(bar_o, 1);
            asm volatile("fence.mbarrier_init.release.cluster;" ::: "memory");
            mbar_expect_tx(bar_q, 1024);
            mbar_expect_tx(bar_o, 7 * 1024);
        }
        __syncthreads();
        if (is_att) cluster_arrive();
        uint32_t* inbox = mail_s + (cta * 2 + a) * (HKV * 32) + lane * 4;
        {
            uint32_t* clr = is_att ? inbox : mail_g + rank * (NB * DM) + a * (NB * DM / 2) + lane * 4;
            const int n = is_att ? 2 : rank < N_FFN ? 16 : 0;
#pragma unroll 1
            for (int i = 0; i < n; i++) st_rlx_zero4(clr + i * 128);
        }
        __syncwarp();
        if (lane == 0) {
            asm volatile("fence.acq_rel.gpu;" ::: "memory");
            atomicInc(&g_ctr, 2 * N_CTA - 1);
            int it = 0;
            while (true) {
                __nanosleep(2000);
                unsigned v;
                asm volatile("ld.acquire.gpu.global.u32 %0, [%1];" : "=r"(v) : "l"(&g_ctr) : "memory");
                if (v == 0u) break;
                if (++it > SPIN_LIMIT) __trap();
            }
            mbar_arrive(bar_ok);
        }
        __syncwarp();
        if (is_att) {
            cluster_wait();
            cluster_arrive();
            const int w = 4 * (lane & 7) + (lane >> 3);
            const int col = rank * 64 + a * 32 + (w & 16) + ((w >> 1) & 7) + 8 * (w & 1);
            const float xv = __bfloat162float(x[hkv * DM + col]);
            const float b2v = __bfloat162float(b2[col]);
            float y;
            int it = 0;
            while (true) {
                uint32_t p[N_FFN], mn = 1u;
#pragma unroll
                for (int i = 0; i < N_FFN; i++) p[i] = ld_rlx(mail_g + (i * NB + hkv) * DM + col);
                y = 0.f;
#pragma unroll
                for (int i = 0; i < N_FFN; i++) { mn = min(mn, p[i]); y += __uint_as_float(p[i]); }
                if (__all_sync(0xffffffffu, mn != 0u)) break;
                __nanosleep(1000);
                if (++it > SPIN_LIMIT) __trap();
            }
            y = rbf(rbf(y) + b2v);
            const float gate = rbf(__fdividef(y, 1.0f + __expf(-y)));
            if (lane == 0) STAMP(8);
            mbar_wait(bar_o, 0);
            if (lane == 0) STAMP(14);
            mbar_wait(bar_full + 8 * ((NT_ATT - 1) % STAGES), ((NT_ATT - 1) / STAGES) & 1);
            uint4 v0 = {}, v1 = {};
            it = 0;
            bool n0 = true, n1 = true;
            do {
                if (n0) v0 = ld_rlx4(inbox);
                if (n1) v1 = ld_rlx4(inbox + 128);
                n0 = min4(v0) == 0u; n1 = min4(v1) == 0u;
                if (++it > SPIN_LIMIT) __trap();
            } while (__any_sync(0xffffffffu, n0 || n1));
            const float s0 = __uint_as_float(v0.x) + __uint_as_float(v1.x), s1 = __uint_as_float(v0.y) + __uint_as_float(v1.y);
            const float s2 = __uint_as_float(v0.z) + __uint_as_float(v1.z), s3 = __uint_as_float(v0.w) + __uint_as_float(v1.w);
            const bool up = lane & 16;
            float k0 = up ? s2 : s0, k1 = up ? s3 : s1;
            k0 += __shfl_xor_sync(0xffffffffu, up ? s0 : s2, 16);
            k1 += __shfl_xor_sync(0xffffffffu, up ? s1 : s3, 16);
            const bool odd = lane & 8;
            float s = odd ? k1 : k0;
            s += __shfl_xor_sync(0xffffffffu, odd ? k0 : k1, 8);
            out[hkv * DM + col] = __float2bfloat16_rn(xv + rbf(rbf(s) * gate));
            if (lane == 0) STAMP(9 + 4 * a);
        }
    } else {
        const int warp = warp_id - 3, tid = threadIdx.x - 96;
        const int g = lane >> 2, t = lane & 3;
        {
            uint4 xv[2];
#pragma unroll
            for (int i = 0; i < 2; i++) xv[i] = __ldg(reinterpret_cast<const uint4*>(x + warp * DM + i * 256 + lane * 8));
            __syncthreads();
            if (is_att) cluster_arrive();
            uint32_t w[8] = {xv[0].x, xv[0].y, xv[0].z, xv[0].w, xv[1].x, xv[1].y, xv[1].z, xv[1].w};
            float s0 = 0.f, s1 = 0.f;
#pragma unroll
            for (int i = 0; i < 8; i++) { s0 += bf_lo(w[i]); s1 += bf_hi(w[i]); }
            s0 += s1;
#pragma unroll
            for (int o = 16; o > 0; o >>= 1) s0 += __shfl_xor_sync(0xffffffffu, s0, o);
            const float mean = s0 * (1.0f / DM);
            s0 = 0.f; s1 = 0.f;
#pragma unroll
            for (int i = 0; i < 8; i++) {
                const float d0 = bf_lo(w[i]) - mean, d1 = bf_hi(w[i]) - mean;
                s0 += d0 * d0; s1 += d1 * d1;
            }
            s0 += s1;
#pragma unroll
            for (int o = 16; o > 0; o >>= 1) s0 += __shfl_xor_sync(0xffffffffu, s0, o);
            const uint32_t mb = pack_bf16(mean, mean);
            float sd;
            asm("sqrt.approx.f32 %0, %1;" : "=f"(sd) : "f"(rbf(rbf(s0 * (1.0f / DM)) + 1e-5f)));
            const float rs = rcp(rbf(sd));
#pragma unroll
            for (int i = 0; i < 8; i++) {
                const uint32_t d = sub_bf16x2(w[i], mb);
                w[i] = pack_bf16(bf_lo(d) * rs, bf_hi(d) * rs);
            }
#pragma unroll
            for (int i = 0; i < 2; i++)
                *reinterpret_cast<uint4*>(sp + SM_XN + (warp * XN_STRIDE + i * 256 + lane * 8) * 2) =
                    make_uint4(w[4 * i], w[4 * i + 1], w[4 * i + 2], w[4 * i + 3]);
        }
        bar_compute();
        const uint32_t* xn32 = reinterpret_cast<const uint32_t*>(sp + SM_XN) + g * (XN_STRIDE / 2) + t;
        const int krow = (lane & 7) + (lane >> 4) * 8;
        const int cbit = (lane >> 3) & 1;
        const int wq4 = warp & 3;
        Cursor cur;

        if (is_att) {
            cluster_wait();
            uint32_t wbase = sb + SM_RING + krow * 128 + (((2 * wq4 + cbit) ^ (lane & 7)) << 4);
            uint32_t abase = sb + SM_XN + (lane & 7) * (XN_STRIDE * 2) + (lane >> 3) * 16;
            if (warp < 4) {
                float r[4];
                project<true>(r, wbase, abase, bar_full, 0, lane);
                const uint32_t q0 = movm_t(pack_bf16(r[0], r[1])), q1 = movm_t(pack_bf16(r[2], r[3]));
                st_async2(mapa(sb + SM_QIN + ((rank * 4 + warp) * 4 + t) * 8, g), q0, q1, mapa(bar_q, g));
            }
            uint2 qf[8];
            mbar_wait_cluster(bar_q, 0);
#pragma unroll
            for (int kk = 0; kk < 8; kk++) qf[kk] = *reinterpret_cast<const uint2*>(sp + SM_QIN + (((g & 3) * 8 + kk) * 4 + t) * 8);
            if (tid == 0) STAMP(3);
            float o[8][4] = {};
            float m0 = -INFINITY, m1 = -INFINITY, l0 = 0.f, l1 = 0.f;
            uint32_t mpk = 0xff80ff80u;
            uint32_t koff[4], voff[4];
#pragma unroll
            for (int i = 0; i < 4; i++) {
                koff[i] = (16 * wq4 + (lane & 7) + cbit * 8) * 128 + (((2 * i + (lane >> 4)) ^ (lane & 7)) << 4);
                voff[i] = (16 * wq4 + krow) * 128 + (((2 * i + cbit) ^ (lane & 7)) << 4);
            }
            constexpr int SLOT_A = (NT_ATT - 8) % STAGES;
            uint32_t part = sb + SM_RING + (SLOT_A + (warp >> 2)) * STAGE_BYTES + wq4 * 2048 + (t & 1) * 1024 + (t >> 1) * 256 + ((g ^ (8 * t)) << 2);
            uint32_t psum = sb + SM_RING + SLOT_A * STAGE_BYTES +
                            ((tid >> 6) * 128 + ((2 * (tid & 63)) ^ (8 * ((tid >> 7) + 2 * ((tid >> 5) & 1))))) * 4;
            uint32_t orow = sb + SM_XN + rank * (XN_STRIDE * 2);
            uint32_t odst = mapa(orow + lane * 16, warp), obar = mapa(bar_o, warp), ost = orow + tid * 4, old = orow + lane * 16;
            uint32_t* sdst = mail_s + (((2 * t * 8 + rank) * 2 + (wq4 >> 1)) * HKV + hkv) * 32 + (warp & 1) * 16 + 2 * g;
            asm volatile("" : "+r"(part), "+r"(psum), "+r"(odst), "+r"(obar), "+r"(ost), "+r"(old), "+l"(sdst), "+r"(wbase), "+r"(abase));
            cur.adv(4 + (warp >> 2));
#pragma unroll 1
            for (int tile = 0; tile < KV_TILES / 2; tile++) {
                const uint32_t kbar = bar_full + 8 * cur.slot, vbar = kbar + 16;
                const uint32_t kb = sb + SM_RING + cur.slot * STAGE_BYTES, vb = kb + 2 * STAGE_BYTES;
                uint32_t a[8][4];
                mbar_wait(kbar, cur.phase);
#pragma unroll
                for (int i = 0; i < 8; i++) ldsm4(a[i], kb + (i >> 2) * 8192 + koff[i & 3]);
                const bool early = mbar_test(vbar, cur.phase);
                float sa[4][4] = {};
#pragma unroll
                for (int i = 0; i < 8; i++) mma16816(sa[i & 3], a[i], qf[i].x, qf[i].y);
                __syncwarp();
                if (lane == 0) mbar_arrive(kbar + 8 * STAGES);
                if (early) {
#pragma unroll
                    for (int i = 0; i < 8; i++) ldsm4t(a[i], vb + (i >> 2) * 8192 + voff[i & 3]);
                }
                uint32_t s01 = pack_bf16((sa[0][0] + sa[1][0]) + (sa[2][0] + sa[3][0]), (sa[0][1] + sa[1][1]) + (sa[2][1] + sa[3][1]));
                uint32_t s23 = pack_bf16((sa[0][2] + sa[1][2]) + (sa[2][2] + sa[3][2]), (sa[0][3] + sa[1][3]) + (sa[2][3] + sa[3][3]));
                const float scale = 0.08838834764831845f;
                s01 = pack_bf16(bf_lo(s01) * scale, bf_hi(s01) * scale);
                s23 = pack_bf16(bf_lo(s23) * scale, bf_hi(s23) * scale);
                uint32_t mx = max_bf16x2(max_bf16x2(s01, s23), mpk);
                if (__any_sync(0xffffffffu, mx != mpk)) {
                    mx = max_bf16x2(mx, __shfl_xor_sync(0xffffffffu, mx, 4));
                    mx = max_bf16x2(mx, __shfl_xor_sync(0xffffffffu, mx, 8));
                    mx = max_bf16x2(mx, __shfl_xor_sync(0xffffffffu, mx, 16));
                    const float n0 = bf_lo(mx), n1 = bf_hi(mx);
                    const float a0 = ex2((m0 - n0) * LOG2E), a1 = ex2((m1 - n1) * LOG2E);
                    m0 = n0; m1 = n1; mpk = mx;
                    l0 *= a0; l1 *= a1;
#pragma unroll
                    for (int mt = 0; mt < 8; mt++) { o[mt][0] *= a0; o[mt][1] *= a1; o[mt][2] *= a0; o[mt][3] *= a1; }
                }
                const float p0 = ex2((bf_lo(s01) - m0) * LOG2E), p1 = ex2((bf_hi(s01) - m1) * LOG2E);
                const float p2 = ex2((bf_lo(s23) - m0) * LOG2E), p3 = ex2((bf_hi(s23) - m1) * LOG2E);
                l0 += p0 + p2; l1 += p1 + p3;
                const uint32_t pb0 = movm_t(pack_bf16(p0, p1)), pb1 = movm_t(pack_bf16(p2, p3));
                if (tile == KV_TILES / 2 - 1) {
#pragma unroll
                    for (int of = 4; of < 32; of <<= 1) {
                        l0 += __shfl_xor_sync(0xffffffffu, l0, of);
                        l1 += __shfl_xor_sync(0xffffffffu, l1, of);
                    }
                    if (lane < 2) *reinterpret_cast<float4*>(sp + SM_ML + warp * 32 + lane * 16) = make_float4(m0, l0, m1, l1);
                    mbar_wait(bar_ok, 0);
                    bar_compute();
                    const float4 ml = *reinterpret_cast<const float4*>(sp + SM_ML + g * 32 + (t & 1) * 16);
                    float M0 = ml.x, M1 = ml.z;
#pragma unroll
                    for (int of = 4; of < 32; of <<= 1) {
                        M0 = fmaxf(M0, __shfl_xor_sync(0xffffffffu, M0, of));
                        M1 = fmaxf(M1, __shfl_xor_sync(0xffffffffu, M1, of));
                    }
                    float L0 = ex2((ml.x - M0) * LOG2E) * ml.y, L1 = ex2((ml.z - M1) * LOG2E) * ml.w;
#pragma unroll
                    for (int of = 4; of < 32; of <<= 1) {
                        L0 += __shfl_xor_sync(0xffffffffu, L0, of);
                        L1 += __shfl_xor_sync(0xffffffffu, L1, of);
                    }
                    l0 = ex2((m0 - M0) * LOG2E) * rcp(L0);
                    l1 = ex2((m1 - M1) * LOG2E) * rcp(L1);
                }
                if (!early) {
                    mbar_wait(vbar, cur.phase);
#pragma unroll
                    for (int i = 0; i < 8; i++) ldsm4t(a[i], vb + (i >> 2) * 8192 + voff[i & 3]);
                }
#pragma unroll
                for (int i = 0; i < 8; i++) mma16816(o[i], a[i], pb0, pb1);
                __syncwarp();
                if (lane == 0) mbar_arrive(vbar + 8 * STAGES);
                cur.adv(4);
            }
            {
                const bool hi = t >= 2;
#pragma unroll
                for (int i = 0; i < 4; i++)
#pragma unroll
                    for (int c = 0; c < 4; c++)
                        sts32((part ^ ((16 * (i & 1) + (c >> 1) * 8) << 2)) + (c & 1) * 512 + (i >> 1) * 128,
                              __float_as_uint((hi ? o[4 + i][c] : o[i][c]) * ((c & 1) ? l1 : l0)));
            }
            bar_compute();
            {
                float2 v[8];
#pragma unroll
                for (int w = 0; w < 8; w++) v[w] = lds64f(psum + (w >> 2) * STAGE_BYTES + (w & 3) * 2048);
                sts32(ost, pack_bf16(((v[0].x + v[1].x) + (v[2].x + v[3].x)) + ((v[4].x + v[5].x) + (v[6].x + v[7].x)),
                                     ((v[0].y + v[1].y) + (v[2].y + v[3].y)) + ((v[4].y + v[5].y) + (v[6].y + v[7].y))));
            }
            if (tid == 0) STAMP(5);
            bar_compute();
            if (warp != rank) {
                const uint4 u0 = lds128(old), u1 = lds128(old + 512);
                st_async4(odst, u0, obar);
                st_async4(odst + 512, u1, obar);
            }
            if (tid == 0) STAMP(6);
            if (warp < 4) {
                float r[4];
                project<false>(r, wbase, abase, bar_full, bar_o, lane);
                st_rlx2(sdst, nz(r[0]), nz(r[2]));
                st_rlx2(sdst + 16 * HKV * 32, nz(r[1]), nz(r[3]));
                if (tid == 0) STAMP(7);
                cluster_wait();
            }
        } else if (rank < N_FFN) {
            if (tid < FS / 8) *reinterpret_cast<uint4*>(sp + SM_QIN + tid * 16) = __ldg(reinterpret_cast<const uint4*>(b1 + FS * rank) + tid);
            float acc[4][4] = {};
#pragma unroll 1
            for (int kt = 0; kt < 16; kt++) {
                mbar_wait(bar_full + 8 * cur.slot, cur.phase);
                const uint32_t base = sb + SM_RING + cur.slot * STAGE_BYTES + (warp >> 1) * 4096 + krow * 128;
#pragma unroll
                for (int ks = 0; ks < 2; ks++) {
                    const uint32_t b0 = xn32[kt * 16 + ks * 8], b1r = xn32[kt * 16 + ks * 8 + 4];
#pragma unroll
                    for (int mt = 0; mt < 2; mt++) {
                        uint32_t a[4];
                        ldsm4t(a, base + ks * 2048 + (((4 * (warp & 1) + 2 * mt + cbit) ^ (lane & 7)) << 4));
                        mma16816(acc[mt], a, b0, b1r);
                    }
                }
                __syncwarp();
                if (lane == 0) mbar_arrive(bar_empty + 8 * cur.slot);
                cur.adv(1);
            }
            bar_compute();
            __nv_bfloat16* hs = reinterpret_cast<__nv_bfloat16*>(sp + SM_H);
            const __nv_bfloat16* b1s = reinterpret_cast<const __nv_bfloat16*>(sp + SM_QIN);
#pragma unroll
            for (int mt = 0; mt < 2; mt++)
#pragma unroll
                for (int c = 0; c < 4; c++) {
                    const int u = warp * 32 + mt * 16 + g + (c >> 1) * 8;
                    const float hv = rbf(rbf(acc[mt][c]) + __bfloat162float(b1s[u]));
                    const float inner = 0.7978845608028654f * (hv + 0.044715f * hv * hv * hv);
                    hs[(2 * t + (c & 1)) * H_STRIDE + u] = __float2bfloat16_rn(0.5f * hv * (1.0f + tanhf(inner)));
                    acc[mt][c] = 0.f;
                }
            bar_compute();
            const uint32_t* h32 = reinterpret_cast<const uint32_t*>(sp + SM_H) + g * (H_STRIDE / 2) + t;
#pragma unroll 1
            for (int kt = 0; kt < 16; kt++) {
                const uint32_t b0 = h32[kt * 8], b1r = h32[kt * 8 + 4];
                mbar_wait(bar_full + 8 * cur.slot, cur.phase);
                const uint32_t base = sb + SM_RING + cur.slot * STAGE_BYTES + warp * 2048 + krow * 128;
#pragma unroll
                for (int mt = 0; mt < 4; mt++) {
                    uint32_t a[4];
                    ldsm4t(a, base + (((2 * mt + cbit) ^ (lane & 7)) << 4));
                    mma16816(acc[mt], a, b0, b1r);
                }
                __syncwarp();
                if (lane == 0) mbar_arrive(bar_empty + 8 * cur.slot);
                cur.adv(1);
            }
            mbar_wait(bar_ok, 0);
            uint32_t* dst = mail_g + (rank * NB + 2 * t) * DM + warp * 64 + g;
#pragma unroll
            for (int mt = 0; mt < 4; mt++)
#pragma unroll
                for (int c = 0; c < 4; c++) st_rlx(dst + 16 * mt + (c >> 1) * 8 + (c & 1) * DM, nz(acc[mt][c]));
            if (tid == 0) STAMP(7);
        }
    }
}

typedef CUresult (*EncodeTiledFn)(CUtensorMap*, CUtensorMapDataType, cuuint32_t, void*, const cuuint64_t*, const cuuint64_t*,
                                  const cuuint32_t*, const cuuint32_t*, CUtensorMapInterleave, CUtensorMapSwizzle,
                                  CUtensorMapL2promotion, CUtensorMapFloatOOBfill);

void encode(EncodeTiledFn fn, CUtensorMap* m, const void* ptr, int rows, int cols, int nrow, int nblk, CUtensorMapL2promotion promo) {
    const cuuint64_t dims[3] = {64, (cuuint64_t)rows, (cuuint64_t)cols / 64}, strides[2] = {(cuuint64_t)cols * 2, 128};
    const cuuint32_t box[3] = {64, (cuuint32_t)nrow, (cuuint32_t)nblk}, es[3] = {1, 1, 1};
    fn(m, CU_TENSOR_MAP_DATA_TYPE_BFLOAT16, 3, const_cast<void*>(ptr), dims, strides, box, es,
       CU_TENSOR_MAP_INTERLEAVE_NONE, CU_TENSOR_MAP_SWIZZLE_128B, promo, CU_TENSOR_MAP_FLOAT_OOB_FILL_NONE);
}

}

#define W_PROMO_ 2
#define KV_PROMO_ 3

extern "C" void kernel_launch(void* const* d_in, const int* in_sizes, int n_in, void* d_out, int out_size) {
    (void)in_sizes; (void)n_in; (void)out_size;
    EncodeTiledFn fn = nullptr;
    cudaDriverEntryPointQueryResult qr;
    cudaGetDriverEntryPoint("cuTensorMapEncodeTiled", (void**)&fn, cudaEnableDefault, &qr);
    cudaFuncSetAttribute(fused_decode_kernel, cudaFuncAttributeMaxDynamicSharedMemorySize, SMEM_BYTES);

    uint32_t *mail_s = nullptr, *mail_g = nullptr;
    cudaGetSymbolAddress((void**)&mail_s, g_s);
    cudaGetSymbolAddress((void**)&mail_g, g_gp);

    Maps maps;
    encode(fn, &maps.m[0], d_in[1], NB * HKV * SK, DH, 64, 2, (CUtensorMapL2promotion)KV_PROMO_);
    encode(fn, &maps.m[1], d_in[2], NB * HKV * SK, DH, 64, 2, (CUtensorMapL2promotion)KV_PROMO_);
    encode(fn, &maps.m[2], d_in[3], DM, HQ * DH, 128, 1, (CUtensorMapL2promotion)W_PROMO_);
    encode(fn, &maps.m[3], d_in[4], HQ * DH, DM, 128, 1, (CUtensorMapL2promotion)W_PROMO_);
    encode(fn, &maps.m[4], d_in[6], DM, FF, 32, 4, CU_TENSOR_MAP_L2_PROMOTION_L2_256B);
    encode(fn, &maps.m[5], d_in[8], FF, DM, 16, 8, CU_TENSOR_MAP_L2_PROMOTION_L2_256B);
    fused_decode_kernel<<<N_CTA, THREADS, SMEM_BYTES>>>(maps, (const __nv_bfloat16*)d_in[0], (const __nv_bfloat16*)d_in[7],
                                                        (const __nv_bfloat16*)d_in[9], (__nv_bfloat16*)d_out, mail_s, mail_g, TAU_);
}
```

```cpp
#include <cuda_runtime.h>
#include <cuda_bf16.h>
#include <cuda.h>
#include <stdint.h>

namespace {

constexpr int NB = 8, DM = 512, HQ = 32, HKV = 8, SK = 4096, DH = 128, FF = 1792;
constexpr int N_ATT = 64, N_FFN = 7, N_CTA = 72;
constexpr int THREADS = 352;
#define D_START_ 4
#define D_MIN_ 4
#define TAU_ 331
#define PACE_OFF_ 36
#define SLIP_ 4
#define D_HI_ 7
constexpr int SLIP = SLIP_, D_HI = D_HI_;
#define WO_GAP_ 12
constexpr int WO_GAP = WO_GAP_;
#define POLL_DELAY_ 300
constexpr int POLL_DELAY = POLL_DELAY_;
#define PREF_BYTES_ 16384
#define PRE_ 2
#define I_GATE_ 112
constexpr int I_GATE = I_GATE_;
#define D_WO_ 3
constexpr int D_WO = D_WO_;
#define I_FAST_ 92
#define TAU2_ 322
constexpr int I_FAST = I_FAST_;
#define FFN_PACE_ 48
constexpr int STAGES = 12, D_START = D_START_, D_MIN = D_MIN_;
constexpr int PACE_OFF = PACE_OFF_, FFN_PACE = FFN_PACE_;
constexpr int STAGE_BYTES = 16384;
constexpr int KV_TILES = 64;
constexpr int NT_ATT = 4 + 2 * KV_TILES + 4;
constexpr int FS = 256;
constexpr int NT_FFN = 32;
constexpr int XN_STRIDE = DM + 8;
constexpr int H_STRIDE = FS + 8;

constexpr int SM_RING = 0;
constexpr int SM_XN = SM_RING + STAGES * STAGE_BYTES;
constexpr int SM_QIN = SM_XN + NB * XN_STRIDE * 2;
constexpr int SM_ML = SM_QIN + 1024;
constexpr int SM_H = SM_ML + 256;
constexpr int SM_BAR = SM_H + NB * H_STRIDE * 2;
constexpr int SM_END = SM_BAR + (2 * STAGES + 6) * 8;
constexpr int SMEM_BYTES = SM_END + 128;
static_assert(SMEM_BYTES <= 232448, "smem");
static_assert(SM_QIN % 16 == 0 && SM_BAR % 8 == 0, "align");

__device__ uint32_t g_s[N_ATT * 2 * HKV * 32];
__device__ uint32_t g_gp[N_FFN * NB * DM];
__device__ unsigned g_ctr;

#define STAMP(k) do {} while (0)

constexpr int SPIN_LIMIT = 1 << 22;

struct Maps { CUtensorMap m[6]; };

__device__ __forceinline__ void mbar_init(uint32_t bar, uint32_t cnt) {
    asm volatile("mbarrier.init.shared::cta.b64 [%0], %1;" ::"r"(bar), "r"(cnt) : "memory");
}
__device__ __forceinline__ void mbar_expect_tx(uint32_t bar, uint32_t bytes) {
    asm volatile("mbarrier.arrive.expect_tx.shared::cta.b64 _, [%0], %1;" ::"r"(bar), "r"(bytes) : "memory");
}
__device__ __forceinline__ void mbar_arrive(uint32_t bar) {
    asm volatile("mbarrier.arrive.shared::cta.b64 _, [%0];" ::"r"(bar) : "memory");
}
__device__ __forceinline__ void mbar_wait(uint32_t bar, uint32_t parity) {
    uint32_t ok;
    int it = 0;
    do {
        asm volatile("{\n.reg .pred p;\nmbarrier.try_wait.parity.shared::cta.b64 p, [%1], %2;\nselp.u32 %0, 1, 0, p;\n}"
                     : "=r"(ok) : "r"(bar), "r"(parity) : "memory");
        if (++it > SPIN_LIMIT) __trap();
    } while (!ok);
}
__device__ __forceinline__ void mbar_wait_cluster(uint32_t bar, uint32_t parity) {
    uint32_t ok;
    int it = 0;
    do {
        asm volatile("{\n.reg .pred p;\nmbarrier.try_wait.parity.relaxed.cluster.shared::cta.b64 p, [%1], %2;\nselp.u32 %0, 1, 0, p;\n}"
                     : "=r"(ok) : "r"(bar), "r"(parity) : "memory");
        if (++it > SPIN_LIMIT) __trap();
    } while (!ok);
    asm volatile("fence.acquire.sync_restrict::shared::cluster.cluster;" ::: "memory");
}
__device__ __forceinline__ bool mbar_test(uint32_t bar, uint32_t parity) {
    uint32_t ok;
    asm volatile("{\n.reg .pred p;\nmbarrier.test_wait.parity.shared::cta.b64 p, [%1], %2;\nselp.u32 %0, 1, 0, p;\n}"
                 : "=r"(ok) : "r"(bar), "r"(parity) : "memory");
    return ok;
}
__device__ __forceinline__ void tma3d(uint32_t dst, const CUtensorMap* m, uint32_t bar, int c1, int c2, uint64_t pol) {
    asm volatile("cp.async.bulk.tensor.3d.shared::cluster.global.mbarrier::complete_tx::bytes.L2::cache_hint [%0], [%1, {%3, %4, %5}], [%2], %6;"
                 ::"r"(dst), "l"(m), "r"(bar), "r"(0), "r"(c1), "r"(c2), "l"(pol) : "memory");
}
__device__ __forceinline__ uint32_t mapa(uint32_t addr, uint32_t rank) {
    uint32_t r;
    asm("mapa.shared::cluster.u32 %0, %1, %2;" : "=r"(r) : "r"(addr), "r"(rank));
    return r;
}
__device__ __forceinline__ void st_async2(uint32_t addr, uint32_t a, uint32_t b, uint32_t bar) {
    asm volatile("st.async.shared::cluster.mbarrier::complete_tx::bytes.v2.b32 [%0], {%1, %2}, [%3];"
                 ::"r"(addr), "r"(a), "r"(b), "r"(bar) : "memory");
}
__device__ __forceinline__ void st_async4(uint32_t addr, const uint4& v, uint32_t bar) {
    asm volatile("st.async.shared::cluster.mbarrier::complete_tx::bytes.v4.b32 [%0], {%1, %2, %3, %4}, [%5];"
                 ::"r"(addr), "r"(v.x), "r"(v.y), "r"(v.z), "r"(v.w), "r"(bar) : "memory");
}
__device__ __forceinline__ void cluster_arrive() { asm volatile("barrier.cluster.arrive.relaxed.aligned;" ::: "memory"); }
__device__ __forceinline__ void cluster_wait() { asm volatile("barrier.cluster.wait.aligned;" ::: "memory"); }
__device__ __forceinline__ void sts32(uint32_t addr, uint32_t v) {
    asm volatile("st.shared.b32 [%0], %1;" ::"r"(addr), "r"(v) : "memory");
}
__device__ __forceinline__ uint4 lds128(uint32_t addr) {
    uint4 v;
    asm volatile("ld.shared.v4.b32 {%0, %1, %2, %3}, [%4];" : "=r"(v.x), "=r"(v.y), "=r"(v.z), "=r"(v.w) : "r"(addr) : "memory");
    return v;
}
__device__ __forceinline__ void ldsm4(uint32_t (&r)[4], uint32_t addr) {
    asm volatile("ldmatrix.sync.aligned.m8n8.x4.shared.b16 {%0, %1, %2, %3}, [%4];"
                 : "=r"(r[0]), "=r"(r[1]), "=r"(r[2]), "=r"(r[3]) : "r"(addr) : "memory");
}
__device__ __forceinline__ void ldsm4t(uint32_t (&r)[4], uint32_t addr) {
    asm volatile("ldmatrix.sync.aligned.m8n8.x4.trans.shared.b16 {%0, %1, %2, %3}, [%4];"
                 : "=r"(r[0]), "=r"(r[1]), "=r"(r[2]), "=r"(r[3]) : "r"(addr) : "memory");
}
__device__ __forceinline__ void mma16816(float (&c)[4], const uint32_t (&a)[4], uint32_t b0, uint32_t b1) {
    asm volatile("mma.sync.aligned.m16n8k16.row.col.f32.bf16.bf16.f32 {%0, %1, %2, %3}, {%4, %5, %6, %7}, {%8, %9}, {%0, %1, %2, %3};"
                 : "+f"(c[0]), "+f"(c[1]), "+f"(c[2]), "+f"(c[3])
                 : "r"(a[0]), "r"(a[1]), "r"(a[2]), "r"(a[3]), "r"(b0), "r"(b1));
}
__device__ __forceinline__ uint32_t movm_t(uint32_t a) {
    uint32_t d;
    asm volatile("movmatrix.sync.aligned.m8n8.trans.b16 %0, %1;" : "=r"(d) : "r"(a));
    return d;
}
__device__ __forceinline__ uint32_t pack_bf16(float lo, float hi) {
    uint32_t d;
    asm("cvt.rn.bf16x2.f32 %0, %1, %2;" : "=r"(d) : "f"(hi), "f"(lo));
    return d;
}
__device__ __forceinline__ float bf_lo(uint32_t v) { return __uint_as_float(v << 16); }
__device__ __forceinline__ float bf_hi(uint32_t v) { return __uint_as_float(v & 0xffff0000u); }
__device__ __forceinline__ float rbf(float x) { return __uint_as_float(pack_bf16(0.f, x)); }
__device__ __forceinline__ uint32_t max_bf16x2(uint32_t a, uint32_t b) {
    uint32_t d;
    asm("max.bf16x2 %0, %1, %2;" : "=r"(d) : "r"(a), "r"(b));
    return d;
}
__device__ __forceinline__ uint32_t sub_bf16x2(uint32_t a, uint32_t b) {
    uint32_t d;
    asm("sub.rn.bf16x2 %0, %1, %2;" : "=r"(d) : "r"(a), "r"(b));
    return d;
}
__device__ __forceinline__ float ex2(float x) {
    float y;
    asm("ex2.approx.ftz.f32 %0, %1;" : "=f"(y) : "f"(x));
    return y;
}
__device__ __forceinline__ float rcp(float x) {
    float y;
    asm("rcp.approx.ftz.f32 %0, %1;" : "=f"(y) : "f"(x));
    return y;
}
__device__ __forceinline__ uint32_t nz(float f) { const uint32_t w = __float_as_uint(f); return w == 0u ? 0x80000000u : w; }
__device__ __forceinline__ void st_rlx(uint32_t* p, uint32_t v) {
    asm volatile("st.relaxed.gpu.global.u32 [%0], %1;" ::"l"(p), "r"(v) : "memory");
}
__device__ __forceinline__ void st_rlx2(uint32_t* p, uint32_t a, uint32_t b) {
    asm volatile("st.relaxed.gpu.global.v2.u32 [%0], {%1, %2};" ::"l"(p), "r"(a), "r"(b) : "memory");
}
__device__ __forceinline__ void st_rlx_zero4(uint32_t* p) {
    asm volatile("st.relaxed.gpu.global.v4.u32 [%0], {%1, %1, %1, %1};" ::"l"(p), "r"(0) : "memory");
}
__device__ __forceinline__ uint32_t ld_rlx(const uint32_t* p) {
    uint32_t v;
    asm volatile("ld.relaxed.gpu.global.u32 %0, [%1];" : "=r"(v) : "l"(p) : "memory");
    return v;
}
__device__ __forceinline__ bool elect_one() {
    uint32_t p;
    asm volatile("{\n.reg .pred P;\nelect.sync _|P, 0xffffffff;\nselp.u32 %0, 1, 0, P;\n}" : "=r"(p));
    return p;
}
__device__ __forceinline__ uint32_t timer_ns() {
    uint32_t t;
    asm volatile("mov.u32 %0, %%globaltimer_lo;" : "=r"(t));
    return t;
}
__device__ __forceinline__ void bar_compute() { asm volatile("bar.sync 1, 256;" ::: "memory"); }

struct Cursor {
    int slot = 0;
    uint32_t phase = 0;
    __device__ __forceinline__ void adv(int n) { slot += n; if (slot >= STAGES) { slot -= STAGES; phase ^= 1u; } }
};

constexpr float LOG2E = 1.4426950408889634f;

template <bool FIRST>
__device__ __forceinline__ void project(float (&r)[4], uint32_t wbase, uint32_t abase, uint32_t bar_full, uint32_t bar_act, int lane) {
    constexpr uint32_t phase = FIRST ? 0 : ((NT_ATT - 4) / STAGES) & 1;
    constexpr int PRE = FIRST ? 0 : PRE_;
    static_assert((NT_ATT - 4) % STAGES == 0, "wo must start in slot 0");
    uint32_t a[4][8][4], bf[4][4][4];
    float acc[4][4] = {};
#pragma unroll
    for (int s = 0; s < PRE; s++) {
        mbar_wait(bar_full + 8 * s, phase);
#pragma unroll
        for (int ks = 0; ks < 8; ks++) ldsm4t(a[s][ks], wbase + s * STAGE_BYTES + ks * 2048);
    }
#pragma unroll
    for (int s = 0; s < 4; s++) {
        if ((s & 1) == 0) {
            if (!FIRST) mbar_wait_cluster(bar_act + 4 * s, 0);
#pragma unroll
            for (int i = 0; i < 8; i++) ldsm4(bf[s + (i >> 2)][i & 3], abase + s * 256 + i * 64);
            if (!FIRST && s == 2) cluster_arrive();
        }
        if (s >= PRE) {
            mbar_wait(bar_full + 8 * s, phase);
#pragma unroll
            for (int ks = 0; ks < 8; ks++) ldsm4t(a[s][ks], wbase + s * STAGE_BYTES + ks * 2048);
        }
#pragma unroll
        for (int ks = 0; ks < 8; ks++) mma16816(acc[ks & 3], a[s][ks], bf[s][ks >> 1][2 * (ks & 1)], bf[s][ks >> 1][2 * (ks & 1) + 1]);
    }
    if (FIRST) {
        __syncwarp();
        if (lane < 4) mbar_arrive(bar_full + 8 * (STAGES + lane));
    }
#pragma unroll
    for (int i = 0; i < 4; i++) r[i] = (acc[0][i] + acc[1][i]) + (acc[2][i] + acc[3][i]);
}

__global__ void __cluster_dims__(8, 1, 1) __launch_bounds__(THREADS, 1)
fused_decode_kernel(const __grid_constant__ Maps maps, const __nv_bfloat16* __restrict__ x, const __nv_bfloat16* __restrict__ b1,
                    const __nv_bfloat16* __restrict__ b2, __nv_bfloat16* __restrict__ out, uint32_t* mail_s, uint32_t* mail_g, const void* wq, const uint32_t tau, const uint32_t tau2) {
    extern __shared__ __align__(1024) uint8_t smem_raw[];
    uint32_t sb;
    asm volatile("{\n.reg .u64 a;\ncvta.to.shared.u64 a, %1;\ncvt.u32.u64 %0, a;\n}" : "=r"(sb) : "l"(smem_raw));
    uint8_t* sp = smem_raw;
    const uint32_t bar_full = sb + SM_BAR, bar_empty = bar_full + 8 * STAGES;
    const uint32_t bar_ok = bar_empty + 8 * STAGES, bar_q = bar_ok + 8, bar_o = bar_q + 8, bar_pub = bar_o + 16, bar_gate = bar_pub + 8;

    if (threadIdx.x == 0 && blockIdx.x < N_ATT)
        asm volatile("cp.async.bulk.prefetch.L2.global [%0], %1;"
                     ::"l"(reinterpret_cast<const char*>(wq) + (size_t)blockIdx.x * PREF_BYTES_), "r"(PREF_BYTES_) : "memory");
    const int warp_id = __shfl_sync(0xffffffffu, (int)(threadIdx.x >> 5), 0), lane = threadIdx.x & 31;
    const int cta = blockIdx.x;
    const bool is_att = cta < N_ATT;
    const int hkv = cta >> 3, rank = cta & 7;

    if (warp_id == 0) {
        const bool leader = elect_one();
        if (leader) STAMP(0);
        uint64_t pol;
        asm volatile("createpolicy.fractional.L2::evict_first.b64 %0, 1.0;" : "=l"(pol));
        const int nt = is_att ? NT_ATT : rank < N_FFN ? NT_FFN : 0;
        const int row0 = (rank * HKV + hkv) * SK - 128;
        auto coords = [&](int i, int& mi, int& c1, int& c2) {
            c2 = 0;
            if (is_att) {
                mi = (i >> 1) & 1; c1 = row0 + (i >> 2) * 128 + (i & 1) * 64;
                if (i < 4) { mi = 2; c1 = 128 * i; c2 = cta; }
                if (i >= NT_ATT - 4) { mi = 3; c1 = 512 * hkv + 128 * (i - (NT_ATT - 4)); c2 = rank; }
            } else {
                mi = 5; c1 = FS * rank + 16 * (i - 16);
                if (i < 16) { mi = 4; c1 = 32 * i; c2 = 4 * rank; }
            }
        };
#pragma unroll
        for (int i = 0; i < D_START; i++)
            if (leader) mbar_init(bar_full + 8 * i, 1);
        if (nt > 0) {
#pragma unroll
            for (int i = 0; i < D_START; i++) {
                int mi, c1, c2;
                coords(i, mi, c1, c2);
                if (leader) {
                    mbar_expect_tx(bar_full + 8 * i, STAGE_BYTES);
                    tma3d(sb + SM_RING + i * STAGE_BYTES, &maps.m[mi], bar_full + 8 * i, c1, c2, pol);
                }
            }
        }
        const uint32_t t0 = timer_ns();
        __syncthreads();
        if (is_att) cluster_arrive();
        Cursor cur, lag, hi;
        cur.slot = D_START;
        lag.slot = D_START - D_MIN;
        const uint32_t step = is_att ? tau : tau * FFN_PACE / 16;
        uint32_t due = t0 + step * PACE_OFF / 16;
#pragma unroll 1
        for (int i = D_START; i < nt; i++) {
            int mi, c1, c2;
            coords(i, mi, c1, c2);
            const CUtensorMap* map = &maps.m[mi];
            const uint32_t dst = sb + SM_RING + cur.slot * STAGE_BYTES, bar = bar_full + 8 * cur.slot;
            const uint32_t lbar = is_att ? bar_full + 8 * lag.slot : bar_q, lph = is_att ? lag.phase : 0u;
            if (i >= STAGES) mbar_wait(bar + 8 * STAGES, cur.phase ^ 1u);
            if (leader) mbar_expect_tx(bar, STAGE_BYTES);
            int it = 0;
#pragma unroll 1
            while (!mbar_test(lbar, lph) && (int)(timer_ns() - due) < 0 && ++it < 4096) {
            }
            if (leader) tma3d(dst, map, bar, c1, c2, pol);
            if (i == I_GATE && leader) mbar_arrive(bar_gate);
            lag.adv(i == NT_ATT - 5 ? 1 + D_MIN - D_WO : 1);
            cur.adv(1);
            due += i >= I_FAST ? tau2 : step;
            if (i == NT_ATT - 5) due += step * WO_GAP / 16;
            if (i >= D_HI) {
                if (!mbar_test(bar_full + 8 * hi.slot, hi.phase)) due += step * SLIP / 16;
                hi.adv(1);
            }
        }
        if (leader) STAMP(1);
    } else if (warp_id < 3) {
        const int a = warp_id - 1;
        if (a == 0 && elect_one()) {
            if (sb & 1023u) __trap();
#pragma unroll
            for (int s = D_START; s < STAGES; s++) mbar_init(bar_full + 8 * s, 1);
#pragma unroll
            for (int s = 0; s < STAGES; s++) mbar_init(bar_empty + 8 * s, is_att ? 4 : 8);
            mbar_init(bar_ok, 2);
            mbar_init(bar_q, 1);
            mbar_init(bar_o, 1);
            mbar_init(bar_o + 8, 1);
            mbar_init(bar_pub, 1);
            mbar_init(bar_gate, 1);
            asm volatile("fence.mbarrier_init.release.cluster;" ::: "memory");
            mbar_expect_tx(bar_q, 1024);
            mbar_expect_tx(bar_o, 7 * 512);
            mbar_expect_tx(bar_o + 8, 7 * 512);
        }
        __syncthreads();
        if (is_att) cluster_arrive();
        const uint32_t* inbox = mail_s + (cta * 2 + a) * (HKV * 32) + lane;
        {
            uint32_t* clr = is_att ? mail_s + ((((4 * a + (lane >> 3)) * 8 + rank) * 2) * HKV + hkv) * 32 + (lane & 7) * 4
                                   : mail_g + rank * (NB * DM) + a * (NB * DM / 2) + lane * 4;
            const int n = is_att ? 2 : rank < N_FFN ? 16 : 0, stride = is_att ? HKV * 32 : 128;
#pragma unroll 1
            for (int i = 0; i < n; i++) st_rlx_zero4(clr + i * stride);
        }
        __syncwarp();
        if (lane == 0) {
            asm volatile("fence.acq_rel.gpu;" ::: "memory");
            atomicInc(&g_ctr, 2 * N_CTA - 1);
            int it = 0;
            while (true) {
                __nanosleep(2000);
                unsigned v;
                asm volatile("ld.acquire.gpu.global.u32 %0, [%1];" : "=r"(v) : "l"(&g_ctr) : "memory");
                if (v == 0u) break;
                if (++it > SPIN_LIMIT) __trap();
            }
            mbar_arrive(bar_ok);
        }
        __syncwarp();
        if (is_att) {
            cluster_wait();
            cluster_arrive();
            const int col = rank * 64 + a * 32 + (lane & 16) + ((lane >> 1) & 7) + 8 * (lane & 1);
            const float xv = __bfloat162float(x[hkv * DM + col]);
            const float b2v = __bfloat162float(b2[col]);
            float y;
            int it = 0;
            mbar_wait(bar_gate, 0);
            while (true) {
                uint32_t p[N_FFN], mn = 1u;
#pragma unroll
                for (int i = 0; i < N_FFN; i++) p[i] = ld_rlx(mail_g + (i * NB + hkv) * DM + col);
                y = 0.f;
#pragma unroll
                for (int i = 0; i < N_FFN; i++) { mn = min(mn, p[i]); y += __uint_as_float(p[i]); }
                if (__all_sync(0xffffffffu, mn != 0u)) break;
                __nanosleep(300);
                if (++it > SPIN_LIMIT) __trap();
            }
            y = rbf(rbf(y) + b2v);
            const float gate = rbf(__fdividef(y, 1.0f + __expf(-y)));
            if (lane == 0) STAMP(8);
            __nv_bfloat16* optr = out + hkv * DM + col;
            mbar_wait(bar_pub, 0);
            if (POLL_DELAY > 0) {
                const long long c0 = clock64();
                while (clock64() - c0 < POLL_DELAY) {}
            }
            uint32_t v[HKV] = {};
            it = 0;
            while (true) {
#pragma unroll
                for (int i = 0; i < HKV; i++)
                    if (v[i] == 0u) v[i] = ld_rlx(inbox + i * 32);
                if (__all_sync(0xffffffffu, min(min(min(v[0], v[1]), min(v[2], v[3])), min(min(v[4], v[5]), min(v[6], v[7]))) != 0u)) break;
                if (++it > SPIN_LIMIT) __trap();
            }
            const float s = ((__uint_as_float(v[0]) + __uint_as_float(v[1])) + (__uint_as_float(v[2]) + __uint_as_float(v[3]))) +
                            ((__uint_as_float(v[4]) + __uint_as_float(v[5])) + (__uint_as_float(v[6]) + __uint_as_float(v[7])));
            *optr = __float2bfloat16_rn(xv + rbf(rbf(s) * gate));
            if (lane == 0) STAMP(9 + 4 * a);
        }
    } else {
        const int warp = warp_id - 3, tid = threadIdx.x - 96;
        const int g = lane >> 2, t = lane & 3;
        {
            uint4 xv[2];
#pragma unroll
            for (int i = 0; i < 2; i++) xv[i] = __ldg(reinterpret_cast<const uint4*>(x + warp * DM + i * 256 + lane * 8));
            __syncthreads();
            if (is_att) cluster_arrive();
            uint32_t w[8] = {xv[0].x, xv[0].y, xv[0].z, xv[0].w, xv[1].x, xv[1].y, xv[1].z, xv[1].w};
            float s0 = 0.f, s1 = 0.f;
#pragma unroll
            for (int i = 0; i < 8; i++) { s0 += bf_lo(w[i]); s1 += bf_hi(w[i]); }
            s0 += s1;
#pragma unroll
            for (int o = 16; o > 0; o >>= 1) s0 += __shfl_xor_sync(0xffffffffu, s0, o);
            const float mean = s0 * (1.0f / DM);
            s0 = 0.f; s1 = 0.f;
#pragma unroll
            for (int i = 0; i < 8; i++) {
                const float d0 = bf_lo(w[i]) - mean, d1 = bf_hi(w[i]) - mean;
                s0 += d0 * d0; s1 += d1 * d1;
            }
            s0 += s1;
#pragma unroll
            for (int o = 16; o > 0; o >>= 1) s0 += __shfl_xor_sync(0xffffffffu, s0, o);
            const uint32_t mb = pack_bf16(mean, mean);
            float sd;
            asm("sqrt.approx.f32 %0, %1;" : "=f"(sd) : "f"(rbf(rbf(s0 * (1.0f / DM)) + 1e-5f)));
            const float rs = rcp(rbf(sd));
#pragma unroll
            for (int i = 0; i < 8; i++) {
                const uint32_t d = sub_bf16x2(w[i], mb);
                w[i] = pack_bf16(bf_lo(d) * rs, bf_hi(d) * rs);
            }
#pragma unroll
            for (int i = 0; i < 2; i++)
                *reinterpret_cast<uint4*>(sp + SM_XN + (warp * XN_STRIDE + i * 256 + lane * 8) * 2) =
                    make_uint4(w[4 * i], w[4 * i + 1], w[4 * i + 2], w[4 * i + 3]);
        }
        bar_compute();
        const uint32_t* xn32 = reinterpret_cast<const uint32_t*>(sp + SM_XN) + g * (XN_STRIDE / 2) + t;
        const int krow = (lane & 7) + (lane >> 4) * 8;
        const int cbit = (lane >> 3) & 1;
        const int wq4 = warp & 3;
        Cursor cur;

        if (is_att) {
            cluster_wait();
            const uint32_t wbase = sb + SM_RING + krow * 128 + (((2 * wq4 + cbit) ^ (lane & 7)) << 4);
            const uint32_t abase = sb + SM_XN + (lane & 7) * (XN_STRIDE * 2) + (lane >> 3) * 16;
            if (warp < 4) {
                float r[4];
                project<true>(r, wbase, abase, bar_full, 0, lane);
                const uint32_t q0 = movm_t(pack_bf16(r[0], r[1])), q1 = movm_t(pack_bf16(r[2], r[3]));
                st_async2(mapa(sb + SM_QIN + ((rank * 4 + warp) * 4 + t) * 8, g), q0, q1, mapa(bar_q, g));
            }
            uint2 qf[8];
            mbar_wait_cluster(bar_q, 0);
#pragma unroll
            for (int kk = 0; kk < 8; kk++) qf[kk] = *reinterpret_cast<const uint2*>(sp + SM_QIN + (((g & 3) * 8 + kk) * 4 + t) * 8);
            if (tid == 0) STAMP(3);
            float o[8][4] = {};
            float m0 = -INFINITY, m1 = -INFINITY, l0 = 0.f, l1 = 0.f;
            uint32_t mpk = 0xff80ff80u;
            uint32_t koff[4], voff[4];
#pragma unroll
            for (int i = 0; i < 4; i++) {
                koff[i] = (16 * wq4 + (lane & 7) + cbit * 8) * 128 + (((2 * i + (lane >> 4)) ^ (lane & 7)) << 4);
                voff[i] = (16 * wq4 + krow) * 128 + (((2 * i + cbit) ^ (lane & 7)) << 4);
            }
            float p0, p1, p2, p3;
            cur.adv(4 + (warp >> 2));
#pragma unroll 1
            for (int tile = 0;; tile++) {
                const bool last = tile == KV_TILES / 2 - 1;
                const uint32_t kbar = bar_full + 8 * cur.slot, vbar = kbar + 16;
                const uint32_t kb = sb + SM_RING + cur.slot * STAGE_BYTES, vb = kb + 2 * STAGE_BYTES;
                uint32_t a[8][4];
                mbar_wait(kbar, cur.phase);
#pragma unroll
                for (int i = 0; i < 8; i++) ldsm4(a[i], kb + (i >> 2) * 8192 + koff[i & 3]);
                const bool early = !last && mbar_test(vbar, cur.phase);
                float sa[4][4] = {};
#pragma unroll
                for (int i = 0; i < 8; i++) mma16816(sa[i & 3], a[i], qf[i].x, qf[i].y);
                __syncwarp();
                if (lane == 0) mbar_arrive(kbar + 8 * STAGES);
                if (early) {
#pragma unroll
                    for (int i = 0; i < 8; i++) ldsm4t(a[i], vb + (i >> 2) * 8192 + voff[i & 3]);
                }
                uint32_t s01 = pack_bf16((sa[0][0] + sa[1][0]) + (sa[2][0] + sa[3][0]), (sa[0][1] + sa[1][1]) + (sa[2][1] + sa[3][1]));
                uint32_t s23 = pack_bf16((sa[0][2] + sa[1][2]) + (sa[2][2] + sa[3][2]), (sa[0][3] + sa[1][3]) + (sa[2][3] + sa[3][3]));
                const float scale = 0.08838834764831845f;
                s01 = pack_bf16(bf_lo(s01) * scale, bf_hi(s01) * scale);
                s23 = pack_bf16(bf_lo(s23) * scale, bf_hi(s23) * scale);
                uint32_t mx = max_bf16x2(max_bf16x2(s01, s23), mpk);
                if (__any_sync(0xffffffffu, mx != mpk)) {
                    mx = max_bf16x2(mx, __shfl_xor_sync(0xffffffffu, mx, 4));
                    mx = max_bf16x2(mx, __shfl_xor_sync(0xffffffffu, mx, 8));
                    mx = max_bf16x2(mx, __shfl_xor_sync(0xffffffffu, mx, 16));
                    const float n0 = bf_lo(mx), n1 = bf_hi(mx);
                    const float a0 = ex2((m0 - n0) * LOG2E), a1 = ex2((m1 - n1) * LOG2E);
                    m0 = n0; m1 = n1; mpk = mx;
                    l0 *= a0; l1 *= a1;
#pragma unroll
                    for (int mt = 0; mt < 8; mt++) { o[mt][0] *= a0; o[mt][1] *= a1; o[mt][2] *= a0; o[mt][3] *= a1; }
                }
                p0 = ex2((bf_lo(s01) - m0) * LOG2E); p1 = ex2((bf_hi(s01) - m1) * LOG2E);
                p2 = ex2((bf_lo(s23) - m0) * LOG2E); p3 = ex2((bf_hi(s23) - m1) * LOG2E);
                l0 += p0 + p2; l1 += p1 + p3;
                if (last) break;
                const uint32_t pb0 = movm_t(pack_bf16(p0, p1)), pb1 = movm_t(pack_bf16(p2, p3));
                if (!early) {
                    mbar_wait(vbar, cur.phase);
#pragma unroll
                    for (int i = 0; i < 8; i++) ldsm4t(a[i], vb + (i >> 2) * 8192 + voff[i & 3]);
                }
#pragma unroll
                for (int i = 0; i < 8; i++) mma16816(o[i], a[i], pb0, pb1);
                __syncwarp();
                if (lane == 0) mbar_arrive(vbar + 8 * STAGES);
                cur.adv(4);
            }
            constexpr int SLOT_K = (NT_ATT - 8) % STAGES;
            constexpr uint32_t PH_LAST = ((NT_ATT - 8) / STAGES) & 1;
            const uint32_t orow = sb + SM_XN + rank * (XN_STRIDE * 2);
            uint32_t* sdst = mail_s + (((2 * t * 8 + rank) * 2 + (wq4 >> 1)) * HKV + hkv) * 32 + (warp & 1) * 16 + 2 * g;
            const bool hi = t >= 2;
            {
                if (lane < 2) sts32(sb + SM_ML + lane * 32 + warp * 4, mpk);
                bar_compute();
                const uint4 ma = lds128(sb + SM_ML + (t & 1) * 32), mb = lds128(sb + SM_ML + (t & 1) * 32 + 16);
                const uint32_t M = max_bf16x2(max_bf16x2(max_bf16x2(ma.x, ma.y), max_bf16x2(ma.z, ma.w)),
                                              max_bf16x2(max_bf16x2(mb.x, mb.y), max_bf16x2(mb.z, mb.w)));
                const float f0 = ex2((m0 - bf_lo(M)) * LOG2E), f1 = ex2((m1 - bf_hi(M)) * LOG2E);
                const uint32_t pb0 = movm_t(pack_bf16(p0 * f0, p1 * f1)), pb1 = movm_t(pack_bf16(p2 * f0, p3 * f1));
                uint8_t* part = sp + SM_RING + (SLOT_K + (warp >> 2)) * STAGE_BYTES + wq4 * 2048 + (t >> 1) * 1024 +
                                ((2 * g + (t & 1)) ^ (4 * ((t >> 1) ^ (warp >> 2)))) * 16;
#pragma unroll
                for (int i = 0; i < 4; i++)
                    *reinterpret_cast<float4*>(part + i * 256) =
                        make_float4((hi ? o[4 + i][0] : o[i][0]) * f0, (hi ? o[4 + i][1] : o[i][1]) * f1,
                                    (hi ? o[4 + i][2] : o[i][2]) * f0, (hi ? o[4 + i][3] : o[i][3]) * f1);
                if (lane < 16) *reinterpret_cast<uint2*>(sp + SM_H + lane * 80 + warp * 8) = make_uint2(pb0, pb1);
                if (!hi) *reinterpret_cast<float2*>(sp + SM_H + 2048 + ((t * 8 + g) * 8 + warp) * 8) = make_float2(l0 * f0, l1 * f1);
            }
            bar_compute();
            {
                uint4 pf[2];
#pragma unroll
                for (int i = 0; i < 2; i++) pf[i] = *reinterpret_cast<const uint4*>(sp + SM_H + (lane & 15) * 80 + (lane >> 4) * 32 + i * 16);
                float acc[2][4] = {};
                const uint8_t* psum = sp + SM_RING + (SLOT_K + (t >> 1)) * STAGE_BYTES + warp * 256 +
                                      ((2 * g + (t & 1)) ^ (4 * ((t >> 1) ^ (warp >> 2)))) * 16;
#pragma unroll
                for (int w = 0; w < 4; w++) {
                    const float4 v = *reinterpret_cast<const float4*>(psum + w * 2048);
                    acc[w & 1][0] += v.x; acc[w & 1][1] += v.y; acc[w & 1][2] += v.z; acc[w & 1][3] += v.w;
                }
                const uint32_t vbase = wbase + (SLOT_K + 2) * STAGE_BYTES + (warp >> 2) * 8192;
                const uint32_t ost = orow + (g & 3) * 256 + warp * 32 + (g >> 2) * 16 + t * 4;
                float i0, i1;
#pragma unroll
                for (int h = 0; h < 2; h++) {
                    uint32_t a[4][4];
                    const bool on = (lane >> 4) == h;
                    mbar_wait(bar_full + 8 * (SLOT_K + 2 + h), PH_LAST);
#pragma unroll
                    for (int ks = 0; ks < 4; ks++) ldsm4t(a[ks], vbase + h * STAGE_BYTES + ks * 2048);
                    mma16816(acc[0], a[0], on ? pf[0].x : 0u, on ? pf[0].y : 0u);
                    mma16816(acc[1], a[1], on ? pf[0].z : 0u, on ? pf[0].w : 0u);
                    mma16816(acc[0], a[2], on ? pf[1].x : 0u, on ? pf[1].y : 0u);
                    mma16816(acc[1], a[3], on ? pf[1].z : 0u, on ? pf[1].w : 0u);
                    if (h == 0) {
                        const uint8_t* ls = sp + SM_H + 2048 + ((t & 1) * 8 + g) * 64 + (t >> 1) * 32;
                        const float4 la = *reinterpret_cast<const float4*>(ls), lb = *reinterpret_cast<const float4*>(ls + 16);
                        float L0 = (la.x + la.z) + (lb.x + lb.z), L1 = (la.y + la.w) + (lb.y + lb.w);
#pragma unroll
                        for (int of = 2; of < 32; of <<= 1) {
                            L0 += __shfl_xor_sync(0xffffffffu, L0, of);
                            L1 += __shfl_xor_sync(0xffffffffu, L1, of);
                        }
                        i0 = rcp(L0); i1 = rcp(L1);
                        mbar_wait(bar_ok, 0);
                    }
                }
                const float c0 = acc[0][0] + acc[1][0], c1 = acc[0][1] + acc[1][1], c2 = acc[0][2] + acc[1][2], c3 = acc[0][3] + acc[1][3];
                const float r0 = (hi ? c2 : c0) + __shfl_xor_sync(0xffffffffu, hi ? c0 : c2, 2);
                const float r1 = (hi ? c3 : c1) + __shfl_xor_sync(0xffffffffu, hi ? c1 : c3, 2);
                sts32(ost, movm_t(pack_bf16(r0 * i0, r1 * i1)));
            }
            if (tid == 0) STAMP(5);
            bar_compute();
            if (warp != rank) {
                const uint4 u0 = lds128(orow + lane * 16), u1 = lds128(orow + lane * 16 + 512);
                const uint32_t odst = mapa(orow + lane * 16, warp), obar = mapa(bar_o, warp);
                st_async4(odst, u0, obar);
                st_async4(odst + 512, u1, obar + 8);
            }
            if (tid == 0) STAMP(6);
            if (warp < 4) {
                float r[4];
                project<false>(r, wbase, abase, bar_full, bar_o, lane);
                st_rlx2(sdst, nz(r[0]), nz(r[2]));
                st_rlx2(sdst + 16 * HKV * 32, nz(r[1]), nz(r[3]));
                if (tid == 0) mbar_arrive(bar_pub);
                if (tid == 0) STAMP(7);
                cluster_wait();
            }
        } else if (rank < N_FFN) {
            if (tid < FS / 8) *reinterpret_cast<uint4*>(sp + SM_QIN + tid * 16) = __ldg(reinterpret_cast<const uint4*>(b1 + FS * rank) + tid);
            float acc[4][4] = {};
#pragma unroll 1
            for (int kt = 0; kt < 16; kt++) {
                mbar_wait(bar_full + 8 * cur.slot, cur.phase);
                const uint32_t base = sb + SM_RING + cur.slot * STAGE_BYTES + (warp >> 1) * 4096 + krow * 128;
#pragma unroll
                for (int ks = 0; ks < 2; ks++) {
                    const uint32_t b0 = xn32[kt * 16 + ks * 8], b1r = xn32[kt * 16 + ks * 8 + 4];
#pragma unroll
                    for (int mt = 0; mt < 2; mt++) {
                        uint32_t a[4];
                        ldsm4t(a, base + ks * 2048 + (((4 * (warp & 1) + 2 * mt + cbit) ^ (lane & 7)) << 4));
                        mma16816(acc[mt], a, b0, b1r);
                    }
                }
                __syncwarp();
                if (lane == 0) mbar_arrive(bar_empty + 8 * cur.slot);
                cur.adv(1);
            }
            bar_compute();
            __nv_bfloat16* hs = reinterpret_cast<__nv_bfloat16*>(sp + SM_H);
            const __nv_bfloat16* b1s = reinterpret_cast<const __nv_bfloat16*>(sp + SM_QIN);
#pragma unroll
            for (int mt = 0; mt < 2; mt++)
#pragma unroll
                for (int c = 0; c < 4; c++) {
                    const int u = warp * 32 + mt * 16 + g + (c >> 1) * 8;
                    const float hv = rbf(rbf(acc[mt][c]) + __bfloat162float(b1s[u]));
                    const float inner = 0.7978845608028654f * (hv + 0.044715f * hv * hv * hv);
                    hs[(2 * t + (c & 1)) * H_STRIDE + u] = __float2bfloat16_rn(0.5f * hv * (1.0f + tanhf(inner)));
                    acc[mt][c] = 0.f;
                }
            bar_compute();
            const uint32_t* h32 = reinterpret_cast<const uint32_t*>(sp + SM_H) + g * (H_STRIDE / 2) + t;
#pragma unroll 1
            for (int kt = 0; kt < 16; kt++) {
                const uint32_t b0 = h32[kt * 8], b1r = h32[kt * 8 + 4];
                mbar_wait(bar_full + 8 * cur.slot, cur.phase);
                const uint32_t base = sb + SM_RING + cur.slot * STAGE_BYTES + warp * 2048 + krow * 128;
#pragma unroll
                for (int mt = 0; mt < 4; mt++) {
                    uint32_t a[4];
                    ldsm4t(a, base + (((2 * mt + cbit) ^ (lane & 7)) << 4));
                    mma16816(acc[mt], a, b0, b1r);
                }
                __syncwarp();
                if (lane == 0) mbar_arrive(bar_empty + 8 * cur.slot);
                cur.adv(1);
            }
            mbar_wait(bar_ok, 0);
            uint32_t* dst = mail_g + (rank * NB + 2 * t) * DM + warp * 64 + g;
#pragma unroll
            for (int mt = 0; mt < 4; mt++)
#pragma unroll
                for (int c = 0; c < 4; c++) st_rlx(dst + 16 * mt + (c >> 1) * 8 + (c & 1) * DM, nz(acc[mt][c]));
            if (tid == 0) STAMP(7);
        }
    }
}

typedef CUresult (*EncodeTiledFn)(CUtensorMap*, CUtensorMapDataType, cuuint32_t, void*, const cuuint64_t*, const cuuint64_t*,
                                  const cuuint32_t*, const cuuint32_t*, CUtensorMapInterleave, CUtensorMapSwizzle,
                                  CUtensorMapL2promotion, CUtensorMapFloatOOBfill);

void encode(EncodeTiledFn fn, CUtensorMap* m, const void* ptr, int rows, int cols, int nrow, int nblk, CUtensorMapL2promotion promo) {
    const cuuint64_t dims[3] = {64, (cuuint64_t)rows, (cuuint64_t)cols / 64}, strides[2] = {(cuuint64_t)cols * 2, 128};
    const cuuint32_t box[3] = {64, (cuuint32_t)nrow, (cuuint32_t)nblk}, es[3] = {1, 1, 1};
    fn(m, CU_TENSOR_MAP_DATA_TYPE_BFLOAT16, 3, const_cast<void*>(ptr), dims, strides, box, es,
       CU_TENSOR_MAP_INTERLEAVE_NONE, CU_TENSOR_MAP_SWIZZLE_128B, promo, CU_TENSOR_MAP_FLOAT_OOB_FILL_NONE);
}

}

#define W_PROMO_ 2
#define KV_PROMO_ 3

extern "C" void kernel_launch(void* const* d_in, const int* in_sizes, int n_in, void* d_out, int out_size) {
    (void)in_sizes; (void)n_in; (void)out_size;
    EncodeTiledFn fn = nullptr;
    cudaDriverEntryPointQueryResult qr;
    cudaGetDriverEntryPoint("cuTensorMapEncodeTiled", (void**)&fn, cudaEnableDefault, &qr);
    cudaFuncSetAttribute(fused_decode_kernel, cudaFuncAttributeMaxDynamicSharedMemorySize, SMEM_BYTES);

    uint32_t *mail_s = nullptr, *mail_g = nullptr;
    cudaGetSymbolAddress((void**)&mail_s, g_s);
    cudaGetSymbolAddress((void**)&mail_g, g_gp);

    int dev = 0, khz = 0, bits = 0;
    cudaGetDevice(&dev);
    cudaDeviceGetAttribute(&khz, cudaDevAttrMemoryClockRate, dev);
    cudaDeviceGetAttribute(&bits, cudaDevAttrGlobalMemoryBusWidth, dev);
    const double rel = (khz > 0 && bits > 0) ? (2619000.0 * 5120.0) / ((double)khz * bits) : 1.0;
    const uint32_t tau = (uint32_t)(TAU_ * rel + 0.5), tau2 = (uint32_t)(TAU2_ * rel + 0.5);

    Maps maps;
    encode(fn, &maps.m[0], d_in[1], NB * HKV * SK, DH, 64, 2, (CUtensorMapL2promotion)KV_PROMO_);
    encode(fn, &maps.m[1], d_in[2], NB * HKV * SK, DH, 64, 2, (CUtensorMapL2promotion)KV_PROMO_);
    encode(fn, &maps.m[2], d_in[3], DM, HQ * DH, 128, 1, (CUtensorMapL2promotion)W_PROMO_);
    encode(fn, &maps.m[3], d_in[4], HQ * DH, DM, 128, 1, (CUtensorMapL2promotion)W_PROMO_);
    encode(fn, &maps.m[4], d_in[6], DM, FF, 32, 4, CU_TENSOR_MAP_L2_PROMOTION_L2_256B);
    encode(fn, &maps.m[5], d_in[8], FF, DM, 16, 8, CU_TENSOR_MAP_L2_PROMOTION_L2_256B);
    fused_decode_kernel<<<N_CTA, THREADS, SMEM_BYTES>>>(maps, (const __nv_bfloat16*)d_in[0], (const __nv_bfloat16*)d_in[7],
                                                        (const __nv_bfloat16*)d_in[9], (__nv_bfloat16*)d_out, mail_s, mail_g, d_in[3], tau, tau2);
}
```

```cpp
#include <cuda_runtime.h>
#include <cuda_bf16.h>
#include <cuda.h>
#include <stdint.h>

namespace {

constexpr int NB = 8, DM = 512, HQ = 32, HKV = 8, SK = 4096, DH = 128, FF = 1792;
constexpr int N_ATT = 64, N_FFN = 7, N_CTA = 72;
constexpr int THREADS = 320;
#define D_START_ 4
#define D_MIN_ 4
#define TAU_ 331
#define PACE_OFF_ 36
#define SLIP_ 1
#define D_HI_ 6
constexpr int SLIP = SLIP_, D_HI = D_HI_;
#define WO_GAP_ 12
constexpr int WO_GAP = WO_GAP_;
#define PREF_BYTES_ 16384
#define PRE_ 2
#define I_GATE_ 104
constexpr int I_GATE = I_GATE_;
#define D_WO_ 3
constexpr int D_WO = D_WO_;
#define I_FAST_ 92
#define TAU2_ 321
constexpr int I_FAST = I_FAST_;
#define FFN_PACE_ 48
constexpr int STAGES = 12, D_START = D_START_, D_MIN = D_MIN_;
constexpr int PACE_OFF = PACE_OFF_, FFN_PACE = FFN_PACE_;
constexpr int STAGE_BYTES = 16384;
constexpr int KV_TILES = 64;
constexpr int NT_ATT = 4 + 2 * KV_TILES + 4;
constexpr int FS = 256;
constexpr int NT_FFN = 32;
constexpr int XN_STRIDE = DM + 8;
constexpr int H_STRIDE = FS + 8;

constexpr int SM_RING = 0;
constexpr int SM_XN = SM_RING + STAGES * STAGE_BYTES;
constexpr int SM_QIN = SM_XN + NB * XN_STRIDE * 2;
constexpr int SM_ML = SM_QIN + 1024;
constexpr int SM_H = SM_ML + 256;
constexpr int SM_GATE = SM_H + NB * H_STRIDE * 2;
constexpr int SM_BAR = SM_GATE + 4096;
constexpr int SM_END = SM_BAR + (2 * STAGES + 6) * 8;
constexpr int SMEM_BYTES = SM_END + 128;
static_assert(SMEM_BYTES <= 232448, "smem");
static_assert(SM_QIN % 16 == 0 && SM_BAR % 8 == 0, "align");

__device__ float4 g_gp[N_FFN * 8 * 4 * 32];
__device__ unsigned g_ctr;

#define STAMP(k) do {} while (0)

constexpr int SPIN_LIMIT = 1 << 22;

struct Maps { CUtensorMap m[6]; };

__device__ __forceinline__ void mbar_init(uint32_t bar, uint32_t cnt) {
    asm volatile("mbarrier.init.shared::cta.b64 [%0], %1;" ::"r"(bar), "r"(cnt) : "memory");
}
__device__ __forceinline__ void mbar_expect_tx(uint32_t bar, uint32_t bytes) {
    asm volatile("mbarrier.arrive.expect_tx.shared::cta.b64 _, [%0], %1;" ::"r"(bar), "r"(bytes) : "memory");
}
__device__ __forceinline__ void mbar_arrive(uint32_t bar) {
    asm volatile("mbarrier.arrive.shared::cta.b64 _, [%0];" ::"r"(bar) : "memory");
}
__device__ __forceinline__ void mbar_wait(uint32_t bar, uint32_t parity) {
    uint32_t ok;
    int it = 0;
    do {
        asm volatile("{\n.reg .pred p;\nmbarrier.try_wait.parity.shared::cta.b64 p, [%1], %2;\nselp.u32 %0, 1, 0, p;\n}"
                     : "=r"(ok) : "r"(bar), "r"(parity) : "memory");
        if (++it > SPIN_LIMIT) __trap();
    } while (!ok);
}
__device__ __forceinline__ void mbar_wait_cluster(uint32_t bar, uint32_t parity) {
    uint32_t ok;
    int it = 0;
    do {
        asm volatile("{\n.reg .pred p;\nmbarrier.try_wait.parity.relaxed.cluster.shared::cta.b64 p, [%1], %2;\nselp.u32 %0, 1, 0, p;\n}"
                     : "=r"(ok) : "r"(bar), "r"(parity) : "memory");
        if (++it > SPIN_LIMIT) __trap();
    } while (!ok);
    asm volatile("fence.acquire.sync_restrict::shared::cluster.cluster;" ::: "memory");
}
__device__ __forceinline__ bool mbar_test(uint32_t bar, uint32_t parity) {
    uint32_t ok;
    asm volatile("{\n.reg .pred p;\nmbarrier.test_wait.parity.shared::cta.b64 p, [%1], %2;\nselp.u32 %0, 1, 0, p;\n}"
                 : "=r"(ok) : "r"(bar), "r"(parity) : "memory");
    return ok;
}
__device__ __forceinline__ void tma3d(uint32_t dst, const CUtensorMap* m, uint32_t bar, int c1, int c2, uint64_t pol) {
    asm volatile("cp.async.bulk.tensor.3d.shared::cluster.global.mbarrier::complete_tx::bytes.L2::cache_hint [%0], [%1, {%3, %4, %5}], [%2], %6;"
                 ::"r"(dst), "l"(m), "r"(bar), "r"(0), "r"(c1), "r"(c2), "l"(pol) : "memory");
}
__device__ __forceinline__ uint32_t mapa(uint32_t addr, uint32_t rank) {
    uint32_t r;
    asm("mapa.shared::cluster.u32 %0, %1, %2;" : "=r"(r) : "r"(addr), "r"(rank));
    return r;
}
__device__ __forceinline__ void st_async2(uint32_t addr, uint32_t a, uint32_t b, uint32_t bar) {
    asm volatile("st.async.shared::cluster.mbarrier::complete_tx::bytes.v2.b32 [%0], {%1, %2}, [%3];"
                 ::"r"(addr), "r"(a), "r"(b), "r"(bar) : "memory");
}
__device__ __forceinline__ void st_async4(uint32_t addr, const uint4& v, uint32_t bar) {
    asm volatile("st.async.shared::cluster.mbarrier::complete_tx::bytes.v4.b32 [%0], {%1, %2, %3, %4}, [%5];"
                 ::"r"(addr), "r"(v.x), "r"(v.y), "r"(v.z), "r"(v.w), "r"(bar) : "memory");
}
__device__ __forceinline__ void cluster_arrive() { asm volatile("barrier.cluster.arrive.relaxed.aligned;" ::: "memory"); }
__device__ __forceinline__ void cluster_wait() { asm volatile("barrier.cluster.wait.aligned;" ::: "memory"); }
__device__ __forceinline__ void sts32(uint32_t addr, uint32_t v) {
    asm volatile("st.shared.b32 [%0], %1;" ::"r"(addr), "r"(v) : "memory");
}
__device__ __forceinline__ uint4 lds128(uint32_t addr) {
    uint4 v;
    asm volatile("ld.shared.v4.b32 {%0, %1, %2, %3}, [%4];" : "=r"(v.x), "=r"(v.y), "=r"(v.z), "=r"(v.w) : "r"(addr) : "memory");
    return v;
}
__device__ __forceinline__ void ldsm4(uint32_t (&r)[4], uint32_t addr) {
    asm volatile("ldmatrix.sync.aligned.m8n8.x4.shared.b16 {%0, %1, %2, %3}, [%4];"
                 : "=r"(r[0]), "=r"(r[1]), "=r"(r[2]), "=r"(r[3]) : "r"(addr) : "memory");
}
__device__ __forceinline__ void ldsm4t(uint32_t (&r)[4], uint32_t addr) {
    asm volatile("ldmatrix.sync.aligned.m8n8.x4.trans.shared.b16 {%0, %1, %2, %3}, [%4];"
                 : "=r"(r[0]), "=r"(r[1]), "=r"(r[2]), "=r"(r[3]) : "r"(addr) : "memory");
}
__device__ __forceinline__ void mma16816(float (&c)[4], const uint32_t (&a)[4], uint32_t b0, uint32_t b1) {
    asm volatile("mma.sync.aligned.m16n8k16.row.col.f32.bf16.bf16.f32 {%0, %1, %2, %3}, {%4, %5, %6, %7}, {%8, %9}, {%0, %1, %2, %3};"
                 : "+f"(c[0]), "+f"(c[1]), "+f"(c[2]), "+f"(c[3])
                 : "r"(a[0]), "r"(a[1]), "r"(a[2]), "r"(a[3]), "r"(b0), "r"(b1));
}
__device__ __forceinline__ uint32_t movm_t(uint32_t a) {
    uint32_t d;
    asm volatile("movmatrix.sync.aligned.m8n8.trans.b16 %0, %1;" : "=r"(d) : "r"(a));
    return d;
}
__device__ __forceinline__ uint32_t pack_bf16(float lo, float hi) {
    uint32_t d;
    asm("cvt.rn.bf16x2.f32 %0, %1, %2;" : "=r"(d) : "f"(hi), "f"(lo));
    return d;
}
__device__ __forceinline__ float bf_lo(uint32_t v) { return __uint_as_float(v << 16); }
__device__ __forceinline__ float bf_hi(uint32_t v) { return __uint_as_float(v & 0xffff0000u); }
__device__ __forceinline__ float rbf(float x) { return __uint_as_float(pack_bf16(0.f, x)); }
__device__ __forceinline__ uint32_t max_bf16x2(uint32_t a, uint32_t b) {
    uint32_t d;
    asm("max.bf16x2 %0, %1, %2;" : "=r"(d) : "r"(a), "r"(b));
    return d;
}
__device__ __forceinline__ uint32_t sub_bf16x2(uint32_t a, uint32_t b) {
    uint32_t d;
    asm("sub.rn.bf16x2 %0, %1, %2;" : "=r"(d) : "r"(a), "r"(b));
    return d;
}
__device__ __forceinline__ float ex2(float x) {
    float y;
    asm("ex2.approx.ftz.f32 %0, %1;" : "=f"(y) : "f"(x));
    return y;
}
__device__ __forceinline__ float rcp(float x) {
    float y;
    asm("rcp.approx.ftz.f32 %0, %1;" : "=f"(y) : "f"(x));
    return y;
}
__device__ __forceinline__ void red_bf16x2(__nv_bfloat16* p, uint32_t v) {
    asm volatile("red.relaxed.gpu.global.add.noftz.bf16x2 [%0], %1;" ::"l"(p), "r"(v) : "memory");
}
__device__ __forceinline__ bool elect_one() {
    uint32_t p;
    asm volatile("{\n.reg .pred P;\nelect.sync _|P, 0xffffffff;\nselp.u32 %0, 1, 0, P;\n}" : "=r"(p));
    return p;
}
__device__ __forceinline__ uint32_t timer_ns() {
    uint32_t t;
    asm volatile("mov.u32 %0, %%globaltimer_lo;" : "=r"(t));
    return t;
}
__device__ __forceinline__ void bar_compute() { asm volatile("bar.sync 1, 256;" ::: "memory"); }

struct Cursor {
    int slot = 0;
    uint32_t phase = 0;
    __device__ __forceinline__ void adv(int n) { slot += n; if (slot >= STAGES) { slot -= STAGES; phase ^= 1u; } }
};

constexpr float LOG2E = 1.4426950408889634f;

template <bool FIRST>
__device__ __forceinline__ void project(float (&r)[4], uint32_t wbase, uint32_t abase, uint32_t bar_full, uint32_t bar_act, int lane) {
    constexpr uint32_t phase = FIRST ? 0 : ((NT_ATT - 4) / STAGES) & 1;
    constexpr int PRE = FIRST ? 0 : PRE_;
    static_assert((NT_ATT - 4) % STAGES == 0, "wo must start in slot 0");
    uint32_t a[4][8][4], bf[4][4][4];
    float acc[4][4] = {};
#pragma unroll
    for (int s = 0; s < PRE; s++) {
        mbar_wait(bar_full + 8 * s, phase);
#pragma unroll
        for (int ks = 0; ks < 8; ks++) ldsm4t(a[s][ks], wbase + s * STAGE_BYTES + ks * 2048);
    }
#pragma unroll
    for (int s = 0; s < 4; s++) {
        if ((s & 1) == 0) {
            if (!FIRST) mbar_wait_cluster(bar_act + 4 * s, 0);
#pragma unroll
            for (int i = 0; i < 8; i++) ldsm4(bf[s + (i >> 2)][i & 3], abase + s * 256 + i * 64);
        }
        if (s >= PRE) {
            mbar_wait(bar_full + 8 * s, phase);
#pragma unroll
            for (int ks = 0; ks < 8; ks++) ldsm4t(a[s][ks], wbase + s * STAGE_BYTES + ks * 2048);
        }
#pragma unroll
        for (int ks = 0; ks < 8; ks++) mma16816(acc[ks & 3], a[s][ks], bf[s][ks >> 1][2 * (ks & 1)], bf[s][ks >> 1][2 * (ks & 1) + 1]);
    }
    if (FIRST) {
        __syncwarp();
        if (lane < 4) mbar_arrive(bar_full + 8 * (STAGES + lane));
    }
#pragma unroll
    for (int i = 0; i < 4; i++) r[i] = (acc[0][i] + acc[1][i]) + (acc[2][i] + acc[3][i]);
}

__global__ void __cluster_dims__(8, 1, 1) __launch_bounds__(THREADS, 1)
fused_decode_kernel(const __grid_constant__ Maps maps, const __nv_bfloat16* __restrict__ x, const __nv_bfloat16* __restrict__ b1,
                    const __nv_bfloat16* __restrict__ b2, __nv_bfloat16* __restrict__ out, const void* wq, const uint32_t tau, const uint32_t tau2) {
    extern __shared__ __align__(1024) uint8_t smem_raw[];
    uint32_t sb;
    asm volatile("{\n.reg .u64 a;\ncvta.to.shared.u64 a, %1;\ncvt.u32.u64 %0, a;\n}" : "=r"(sb) : "l"(smem_raw));
    uint8_t* sp = smem_raw;
    const uint32_t bar_full = sb + SM_BAR, bar_empty = bar_full + 8 * STAGES;
    const uint32_t bar_ok = bar_empty + 8 * STAGES, bar_q = bar_ok + 8, bar_o = bar_q + 8, bar_gate = bar_o + 16;

    if (threadIdx.x == 0 && blockIdx.x < N_ATT)
        asm volatile("cp.async.bulk.prefetch.L2.global [%0], %1;"
                     ::"l"(reinterpret_cast<const char*>(wq) + (size_t)blockIdx.x * PREF_BYTES_), "r"(PREF_BYTES_) : "memory");
    const int warp_id = __shfl_sync(0xffffffffu, (int)(threadIdx.x >> 5), 0), lane = threadIdx.x & 31;
    const int cta = blockIdx.x;
    const bool is_att = cta < N_ATT;
    const int hkv = cta >> 3, rank = cta & 7;

    if (warp_id == 0) {
        const bool leader = elect_one();
        if (leader) STAMP(0);
        uint64_t pol;
        asm volatile("createpolicy.fractional.L2::evict_first.b64 %0, 1.0;" : "=l"(pol));
        const int nt = is_att ? NT_ATT : rank < N_FFN ? NT_FFN : 0;
        const int row0 = (rank * HKV + hkv) * SK - 128;
        auto coords = [&](int i, int& mi, int& c1, int& c2) {
            c2 = 0;
            if (is_att) {
                mi = (i >> 1) & 1; c1 = row0 + (i >> 2) * 128 + (i & 1) * 64;
                if (i < 4) { mi = 2; c1 = 128 * i; c2 = cta; }
                if (i >= NT_ATT - 4) { mi = 3; c1 = 512 * hkv + 128 * (i - (NT_ATT - 4)); c2 = rank; }
            } else {
                mi = 5; c1 = FS * rank + 16 * (i - 16);
                if (i < 16) { mi = 4; c1 = 32 * i; c2 = 4 * rank; }
            }
        };
#pragma unroll
        for (int i = 0; i < D_START; i++)
            if (leader) mbar_init(bar_full + 8 * i, 1);
        if (nt > 0) {
#pragma unroll
            for (int i = 0; i < D_START; i++) {
                int mi, c1, c2;
                coords(i, mi, c1, c2);
                if (leader) {
                    mbar_expect_tx(bar_full + 8 * i, STAGE_BYTES);
                    tma3d(sb + SM_RING + i * STAGE_BYTES, &maps.m[mi], bar_full + 8 * i, c1, c2, pol);
                }
            }
        }
        const uint32_t t0 = timer_ns();
        __syncthreads();
        if (is_att) cluster_arrive();
        Cursor cur, lag, hi;
        cur.slot = D_START;
        lag.slot = D_START - D_MIN;
        const uint32_t step = is_att ? tau : tau * FFN_PACE / 16;
        uint32_t due = t0 + step * PACE_OFF / 16;
#pragma unroll 1
        for (int i = D_START; i < nt; i++) {
            int mi, c1, c2;
            coords(i, mi, c1, c2);
            const CUtensorMap* map = &maps.m[mi];
            const uint32_t dst = sb + SM_RING + cur.slot * STAGE_BYTES, bar = bar_full + 8 * cur.slot;
            const uint32_t lbar = is_att ? bar_full + 8 * lag.slot : bar_q, lph = is_att ? lag.phase : 0u;
            if (i >= STAGES) mbar_wait(bar + 8 * STAGES, cur.phase ^ 1u);
            if (leader) mbar_expect_tx(bar, STAGE_BYTES);
            int it = 0;
#pragma unroll 1
            while (!mbar_test(lbar, lph) && (int)(timer_ns() - due) < 0 && ++it < 4096) {
            }
            if (leader) tma3d(dst, map, bar, c1, c2, pol);
            if (i == I_GATE && leader) mbar_arrive(bar_gate);
            lag.adv(i == NT_ATT - 5 ? 1 + D_MIN - D_WO : 1);
            cur.adv(1);
            due += i >= I_FAST ? tau2 : step;
            if (i == NT_ATT - 5) due += step * WO_GAP / 16;
            if (i >= D_HI) {
                if (!mbar_test(bar_full + 8 * hi.slot, hi.phase)) due += step * SLIP / 16;
                hi.adv(1);
            }
        }
        if (leader) STAMP(1);
    } else if (warp_id == 1) {
        if (elect_one()) {
            if (sb & 1023u) __trap();
#pragma unroll
            for (int s = D_START; s < STAGES; s++) mbar_init(bar_full + 8 * s, 1);
#pragma unroll
            for (int s = 0; s < STAGES; s++) mbar_init(bar_empty + 8 * s, is_att ? 4 : 8);
            mbar_init(bar_ok, 1);
            mbar_init(bar_q, 1);
            mbar_init(bar_o, 1);
            mbar_init(bar_o + 8, 1);
            mbar_init(bar_gate, 1);
            asm volatile("fence.mbarrier_init.release.cluster;" ::: "memory");
            mbar_expect_tx(bar_q, 1024);
            mbar_expect_tx(bar_o, 7 * 512);
            mbar_expect_tx(bar_o + 8, 7 * 512);
        }
        __syncthreads();
        if (is_att) {
            cluster_arrive();
            mbar_wait(bar_gate, 0);
            if (lane == 0) {
                int it = 0;
                while (true) {
                    unsigned v;
                    asm volatile("ld.acquire.gpu.global.u32 %0, [%1];" : "=r"(v) : "l"(&g_ctr) : "memory");
                    if (v >= 8u) break;
                    __nanosleep(200);
                    if (++it > SPIN_LIMIT) __trap();
                }
            }
            __syncwarp();
            const int g = lane >> 2, t = lane & 3;
#pragma unroll 2
            for (int mt = 0; mt < 4; mt++) {
                const int col = rank * 64 + mt * 16 + g;
                float y[4] = {}, res[4];
#pragma unroll
                for (int i = 0; i < N_FFN; i++) {
                    const float4 v = __ldcg(g_gp + ((i * 8 + rank) * 4 + mt) * 32 + lane);
                    y[0] += v.x; y[1] += v.y; y[2] += v.z; y[3] += v.w;
                }
#pragma unroll
                for (int c = 0; c < 4; c++) {
                    const int cc = col + 8 * (c >> 1), bb = 2 * t + (c & 1);
                    const float z = rbf(rbf(y[c]) + __bfloat162float(b2[cc]));
                    y[c] = rbf(__fdividef(z, 1.0f + __expf(-z)));
                    res[c] = bb == hkv ? __bfloat162float(x[bb * DM + cc]) : 0.f;
                }
                *reinterpret_cast<float4*>(sp + SM_GATE + mt * 1024 + lane * 16) = make_float4(y[0], y[1], y[2], y[3]);
                *reinterpret_cast<float4*>(sp + SM_GATE + mt * 1024 + 512 + lane * 16) = make_float4(res[0], res[1], res[2], res[3]);
            }
            __syncwarp();
            if (lane == 0) {
                mbar_arrive(bar_ok);
                atomicInc(&g_ctr, N_CTA - 1);
                STAMP(8);
            }
        } else if (rank == N_FFN) {
#pragma unroll 4
            for (int i = 0; i < 16; i++) reinterpret_cast<uint4*>(out)[i * 32 + lane] = make_uint4(0, 0, 0, 0);
            __syncwarp();
            if (lane == 0) {
                asm volatile("fence.acq_rel.gpu;" ::: "memory");
                atomicInc(&g_ctr, N_CTA - 1);
            }
        }
    } else {
        const int warp = warp_id - 2, tid = threadIdx.x - 64;
        const int g = lane >> 2, t = lane & 3;
        {
            uint4 xv[2];
#pragma unroll
            for (int i = 0; i < 2; i++) xv[i] = __ldg(reinterpret_cast<const uint4*>(x + warp * DM + i * 256 + lane * 8));
            __syncthreads();
            if (is_att) cluster_arrive();
            uint32_t w[8] = {xv[0].x, xv[0].y, xv[0].z, xv[0].w, xv[1].x, xv[1].y, xv[1].z, xv[1].w};
            float s0 = 0.f, s1 = 0.f;
#pragma unroll
            for (int i = 0; i < 8; i++) { s0 += bf_lo(w[i]); s1 += bf_hi(w[i]); }
            s0 += s1;
#pragma unroll
            for (int o = 16; o > 0; o >>= 1) s0 += __shfl_xor_sync(0xffffffffu, s0, o);
            const float mean = s0 * (1.0f / DM);
            s0 = 0.f; s1 = 0.f;
#pragma unroll
            for (int i = 0; i < 8; i++) {
                const float d0 = bf_lo(w[i]) - mean, d1 = bf_hi(w[i]) - mean;
                s0 += d0 * d0; s1 += d1 * d1;
            }
            s0 += s1;
#pragma unroll
            for (int o = 16; o > 0; o >>= 1) s0 += __shfl_xor_sync(0xffffffffu, s0, o);
            const uint32_t mb = pack_bf16(mean, mean);
            float sd;
            asm("sqrt.approx.f32 %0, %1;" : "=f"(sd) : "f"(rbf(rbf(s0 * (1.0f / DM)) + 1e-5f)));
            const float rs = rcp(rbf(sd));
#pragma unroll
            for (int i = 0; i < 8; i++) {
                const uint32_t d = sub_bf16x2(w[i], mb);
                w[i] = pack_bf16(bf_lo(d) * rs, bf_hi(d) * rs);
            }
#pragma unroll
            for (int i = 0; i < 2; i++)
                *reinterpret_cast<uint4*>(sp + SM_XN + (warp * XN_STRIDE + i * 256 + lane * 8) * 2) =
                    make_uint4(w[4 * i], w[4 * i + 1], w[4 * i + 2], w[4 * i + 3]);
        }
        bar_compute();
        const uint32_t* xn32 = reinterpret_cast<const uint32_t*>(sp + SM_XN) + g * (XN_STRIDE / 2) + t;
        const int krow = (lane & 7) + (lane >> 4) * 8;
        const int cbit = (lane >> 3) & 1;
        const int wq4 = warp & 3;
        Cursor cur;

        if (is_att) {
            cluster_wait();
            const uint32_t wbase = sb + SM_RING + krow * 128 + (((2 * wq4 + cbit) ^ (lane & 7)) << 4);
            const uint32_t abase = sb + SM_XN + (lane & 7) * (XN_STRIDE * 2) + (lane >> 3) * 16;
            if (warp < 4) {
                float r[4];
                project<true>(r, wbase, abase, bar_full, 0, lane);
                const uint32_t q0 = movm_t(pack_bf16(r[0], r[1])), q1 = movm_t(pack_bf16(r[2], r[3]));
                st_async2(mapa(sb + SM_QIN + ((rank * 4 + warp) * 4 + t) * 8, g), q0, q1, mapa(bar_q, g));
            }
            uint2 qf[8];
            mbar_wait_cluster(bar_q, 0);
#pragma unroll
            for (int kk = 0; kk < 8; kk++) qf[kk] = *reinterpret_cast<const uint2*>(sp + SM_QIN + (((g & 3) * 8 + kk) * 4 + t) * 8);
            if (tid == 0) STAMP(3);
            float o[8][4] = {};
            float m0 = -INFINITY, m1 = -INFINITY, l0 = 0.f, l1 = 0.f;
            uint32_t mpk = 0xff80ff80u;
            uint32_t koff[4], voff[4];
#pragma unroll
            for (int i = 0; i < 4; i++) {
                koff[i] = (16 * wq4 + (lane & 7) + cbit * 8) * 128 + (((2 * i + (lane >> 4)) ^ (lane & 7)) << 4);
                voff[i] = (16 * wq4 + krow) * 128 + (((2 * i + cbit) ^ (lane & 7)) << 4);
            }
            float p0, p1, p2, p3;
            cur.adv(4 + (warp >> 2));
#pragma unroll 1
            for (int tile = 0;; tile++) {
                const bool last = tile == KV_TILES / 2 - 1;
                const uint32_t kbar = bar_full + 8 * cur.slot, vbar = kbar + 16;
                const uint32_t kb = sb + SM_RING + cur.slot * STAGE_BYTES, vb = kb + 2 * STAGE_BYTES;
                uint32_t a[8][4];
                mbar_wait(kbar, cur.phase);
#pragma unroll
                for (int i = 0; i < 8; i++) ldsm4(a[i], kb + (i >> 2) * 8192 + koff[i & 3]);
                const bool early = !last && mbar_test(vbar, cur.phase);
                float sa[4][4] = {};
#pragma unroll
                for (int i = 0; i < 8; i++) mma16816(sa[i & 3], a[i], qf[i].x, qf[i].y);
                __syncwarp();
                if (lane == 0) mbar_arrive(kbar + 8 * STAGES);
                if (early) {
#pragma unroll
                    for (int i = 0; i < 8; i++) ldsm4t(a[i], vb + (i >> 2) * 8192 + voff[i & 3]);
                }
                uint32_t s01 = pack_bf16((sa[0][0] + sa[1][0]) + (sa[2][0] + sa[3][0]), (sa[0][1] + sa[1][1]) + (sa[2][1] + sa[3][1]));
                uint32_t s23 = pack_bf16((sa[0][2] + sa[1][2]) + (sa[2][2] + sa[3][2]), (sa[0][3] + sa[1][3]) + (sa[2][3] + sa[3][3]));
                const float scale = 0.08838834764831845f;
                s01 = pack_bf16(bf_lo(s01) * scale, bf_hi(s01) * scale);
                s23 = pack_bf16(bf_lo(s23) * scale, bf_hi(s23) * scale);
                uint32_t mx = max_bf16x2(max_bf16x2(s01, s23), mpk);
                if (__any_sync(0xffffffffu, mx != mpk)) {
                    mx = max_bf16x2(mx, __shfl_xor_sync(0xffffffffu, mx, 4));
                    mx = max_bf16x2(mx, __shfl_xor_sync(0xffffffffu, mx, 8));
                    mx = max_bf16x2(mx, __shfl_xor_sync(0xffffffffu, mx, 16));
                    const float n0 = bf_lo(mx), n1 = bf_hi(mx);
                    const float a0 = ex2((m0 - n0) * LOG2E), a1 = ex2((m1 - n1) * LOG2E);
                    m0 = n0; m1 = n1; mpk = mx;
                    l0 *= a0; l1 *= a1;
#pragma unroll
                    for (int mt = 0; mt < 8; mt++) { o[mt][0] *= a0; o[mt][1] *= a1; o[mt][2] *= a0; o[mt][3] *= a1; }
                }
                p0 = ex2((bf_lo(s01) - m0) * LOG2E); p1 = ex2((bf_hi(s01) - m1) * LOG2E);
                p2 = ex2((bf_lo(s23) - m0) * LOG2E); p3 = ex2((bf_hi(s23) - m1) * LOG2E);
                l0 += p0 + p2; l1 += p1 + p3;
                if (last) break;
                const uint32_t pb0 = movm_t(pack_bf16(p0, p1)), pb1 = movm_t(pack_bf16(p2, p3));
                if (!early) {
                    mbar_wait(vbar, cur.phase);
#pragma unroll
                    for (int i = 0; i < 8; i++) ldsm4t(a[i], vb + (i >> 2) * 8192 + voff[i & 3]);
                }
#pragma unroll
                for (int i = 0; i < 8; i++) mma16816(o[i], a[i], pb0, pb1);
                __syncwarp();
                if (lane == 0) mbar_arrive(vbar + 8 * STAGES);
                cur.adv(4);
            }
            constexpr int SLOT_K = (NT_ATT - 8) % STAGES;
            constexpr uint32_t PH_LAST = ((NT_ATT - 8) / STAGES) & 1;
            const uint32_t orow = sb + SM_XN + rank * (XN_STRIDE * 2);
            const bool hi = t >= 2;
            {
                if (lane < 2) sts32(sb + SM_ML + lane * 32 + warp * 4, mpk);
                bar_compute();
                const uint4 ma = lds128(sb + SM_ML + (t & 1) * 32), mb = lds128(sb + SM_ML + (t & 1) * 32 + 16);
                const uint32_t M = max_bf16x2(max_bf16x2(max_bf16x2(ma.x, ma.y), max_bf16x2(ma.z, ma.w)),
                                              max_bf16x2(max_bf16x2(mb.x, mb.y), max_bf16x2(mb.z, mb.w)));
                const float f0 = ex2((m0 - bf_lo(M)) * LOG2E), f1 = ex2((m1 - bf_hi(M)) * LOG2E);
                const uint32_t pb0 = movm_t(pack_bf16(p0 * f0, p1 * f1)), pb1 = movm_t(pack_bf16(p2 * f0, p3 * f1));
                uint8_t* part = sp + SM_RING + (SLOT_K + (warp >> 2)) * STAGE_BYTES + wq4 * 2048 + (t >> 1) * 1024 +
                                ((2 * g + (t & 1)) ^ (4 * ((t >> 1) ^ (warp >> 2)))) * 16;
#pragma unroll
                for (int i = 0; i < 4; i++)
                    *reinterpret_cast<float4*>(part + i * 256) =
                        make_float4((hi ? o[4 + i][0] : o[i][0]) * f0, (hi ? o[4 + i][1] : o[i][1]) * f1,
                                    (hi ? o[4 + i][2] : o[i][2]) * f0, (hi ? o[4 + i][3] : o[i][3]) * f1);
                if (lane < 16) *reinterpret_cast<uint2*>(sp + SM_H + lane * 80 + warp * 8) = make_uint2(pb0, pb1);
                if (!hi) *reinterpret_cast<float2*>(sp + SM_H + 2048 + ((t * 8 + g) * 8 + warp) * 8) = make_float2(l0 * f0, l1 * f1);
            }
            bar_compute();
            {
                uint4 pf[2];
#pragma unroll
                for (int i = 0; i < 2; i++) pf[i] = *reinterpret_cast<const uint4*>(sp + SM_H + (lane & 15) * 80 + (lane >> 4) * 32 + i * 16);
                float acc[2][4] = {};
                const uint8_t* psum = sp + SM_RING + (SLOT_K + (t >> 1)) * STAGE_BYTES + warp * 256 +
                                      ((2 * g + (t & 1)) ^ (4 * ((t >> 1) ^ (warp >> 2)))) * 16;
#pragma unroll
                for (int w = 0; w < 4; w++) {
                    const float4 v = *reinterpret_cast<const float4*>(psum + w * 2048);
                    acc[w & 1][0] += v.x; acc[w & 1][1] += v.y; acc[w & 1][2] += v.z; acc[w & 1][3] += v.w;
                }
                const uint32_t vbase = wbase + (SLOT_K + 2) * STAGE_BYTES + (warp >> 2) * 8192;
                const uint32_t ost = orow + (g & 3) * 256 + warp * 32 + (g >> 2) * 16 + t * 4;
                float i0, i1;
#pragma unroll
                for (int h = 0; h < 2; h++) {
                    uint32_t a[4][4];
                    const bool on = (lane >> 4) == h;
                    mbar_wait(bar_full + 8 * (SLOT_K + 2 + h), PH_LAST);
#pragma unroll
                    for (int ks = 0; ks < 4; ks++) ldsm4t(a[ks], vbase + h * STAGE_BYTES + ks * 2048);
                    mma16816(acc[0], a[0], on ? pf[0].x : 0u, on ? pf[0].y : 0u);
                    mma16816(acc[1], a[1], on ? pf[0].z : 0u, on ? pf[0].w : 0u);
                    mma16816(acc[0], a[2], on ? pf[1].x : 0u, on ? pf[1].y : 0u);
                    mma16816(acc[1], a[3], on ? pf[1].z : 0u, on ? pf[1].w : 0u);
                    if (h == 0) {
                        const uint8_t* ls = sp + SM_H + 2048 + ((t & 1) * 8 + g) * 64 + (t >> 1) * 32;
                        const float4 la = *reinterpret_cast<const float4*>(ls), lb = *reinterpret_cast<const float4*>(ls + 16);
                        float L0 = (la.x + la.z) + (lb.x + lb.z), L1 = (la.y + la.w) + (lb.y + lb.w);
#pragma unroll
                        for (int of = 2; of < 32; of <<= 1) {
                            L0 += __shfl_xor_sync(0xffffffffu, L0, of);
                            L1 += __shfl_xor_sync(0xffffffffu, L1, of);
                        }
                        i0 = rcp(L0); i1 = rcp(L1);
                    }
                }
                const float c0 = acc[0][0] + acc[1][0], c1 = acc[0][1] + acc[1][1], c2 = acc[0][2] + acc[1][2], c3 = acc[0][3] + acc[1][3];
                const float r0 = (hi ? c2 : c0) + __shfl_xor_sync(0xffffffffu, hi ? c0 : c2, 2);
                const float r1 = (hi ? c3 : c1) + __shfl_xor_sync(0xffffffffu, hi ? c1 : c3, 2);
                sts32(ost, movm_t(pack_bf16(r0 * i0, r1 * i1)));
            }
            if (tid == 0) STAMP(5);
            bar_compute();
            if (warp != rank) {
                const uint4 u0 = lds128(orow + lane * 16), u1 = lds128(orow + lane * 16 + 512);
                const uint32_t odst = mapa(orow + lane * 16, warp), obar = mapa(bar_o, warp);
                st_async4(odst, u0, obar);
                st_async4(odst + 512, u1, obar + 8);
            }
            if (tid == 0) STAMP(6);
            if (warp < 4) {
                mbar_wait(bar_ok, 0);
                const uint4 gt = lds128(sb + SM_GATE + warp * 1024 + lane * 16), rs = lds128(sb + SM_GATE + warp * 1024 + 512 + lane * 16);
                __nv_bfloat16* dst = out + g * DM + rank * 64 + warp * 16 + 2 * t;
                float r[4];
                project<false>(r, wbase, abase, bar_full, bar_o, lane);
                red_bf16x2(dst, movm_t(pack_bf16(fmaf(r[0], __uint_as_float(gt.x), __uint_as_float(rs.x)),
                                                 fmaf(r[1], __uint_as_float(gt.y), __uint_as_float(rs.y)))));
                red_bf16x2(dst + 8, movm_t(pack_bf16(fmaf(r[2], __uint_as_float(gt.z), __uint_as_float(rs.z)),
                                                     fmaf(r[3], __uint_as_float(gt.w), __uint_as_float(rs.w)))));
                if (tid == 0) STAMP(7);
            }
        } else if (rank < N_FFN) {
            if (tid < FS / 8) *reinterpret_cast<uint4*>(sp + SM_QIN + tid * 16) = __ldg(reinterpret_cast<const uint4*>(b1 + FS * rank) + tid);
            float acc[4][4] = {};
#pragma unroll 1
            for (int kt = 0; kt < 16; kt++) {
                mbar_wait(bar_full + 8 * cur.slot, cur.phase);
                const uint32_t base = sb + SM_RING + cur.slot * STAGE_BYTES + (warp >> 1) * 4096 + krow * 128;
#pragma unroll
                for (int ks = 0; ks < 2; ks++) {
                    const uint32_t b0 = xn32[kt * 16 + ks * 8], b1r = xn32[kt * 16 + ks * 8 + 4];
#pragma unroll
                    for (int mt = 0; mt < 2; mt++) {
                        uint32_t a[4];
                        ldsm4t(a, base + ks * 2048 + (((4 * (warp & 1) + 2 * mt + cbit) ^ (lane & 7)) << 4));
                        mma16816(acc[mt], a, b0, b1r);
                    }
                }
                __syncwarp();
                if (lane == 0) mbar_arrive(bar_empty + 8 * cur.slot);
                cur.adv(1);
            }
            bar_compute();
            __nv_bfloat16* hs = reinterpret_cast<__nv_bfloat16*>(sp + SM_H);
            const __nv_bfloat16* b1s = reinterpret_cast<const __nv_bfloat16*>(sp + SM_QIN);
#pragma unroll
            for (int mt = 0; mt < 2; mt++)
#pragma unroll
                for (int c = 0; c < 4; c++) {
                    const int u = warp * 32 + mt * 16 + g + (c >> 1) * 8;
                    const float hv = rbf(rbf(acc[mt][c]) + __bfloat162float(b1s[u]));
                    const float inner = 0.7978845608028654f * (hv + 0.044715f * hv * hv * hv);
                    hs[(2 * t + (c & 1)) * H_STRIDE + u] = __float2bfloat16_rn(0.5f * hv * (1.0f + tanhf(inner)));
                    acc[mt][c] = 0.f;
                }
            bar_compute();
            const uint32_t* h32 = reinterpret_cast<const uint32_t*>(sp + SM_H) + g * (H_STRIDE / 2) + t;
#pragma unroll 1
            for (int kt = 0; kt < 16; kt++) {
                const uint32_t b0 = h32[kt * 8], b1r = h32[kt * 8 + 4];
                mbar_wait(bar_full + 8 * cur.slot, cur.phase);
                const uint32_t base = sb + SM_RING + cur.slot * STAGE_BYTES + warp * 2048 + krow * 128;
#pragma unroll
                for (int mt = 0; mt < 4; mt++) {
                    uint32_t a[4];
                    ldsm4t(a, base + (((2 * mt + cbit) ^ (lane & 7)) << 4));
                    mma16816(acc[mt], a, b0, b1r);
                }
                __syncwarp();
                if (lane == 0) mbar_arrive(bar_empty + 8 * cur.slot);
                cur.adv(1);
            }
#pragma unroll
            for (int mt = 0; mt < 4; mt++)
                g_gp[((rank * 8 + warp) * 4 + mt) * 32 + lane] = make_float4(acc[mt][0], acc[mt][1], acc[mt][2], acc[mt][3]);
            bar_compute();
            if (tid == 0) {
                asm volatile("fence.acq_rel.gpu;" ::: "memory");
                atomicInc(&g_ctr, N_CTA - 1);
            }
            if (tid == 0) STAMP(7);
        }
    }
}

typedef CUresult (*EncodeTiledFn)(CUtensorMap*, CUtensorMapDataType, cuuint32_t, void*, const cuuint64_t*, const cuuint64_t*,
                                  const cuuint32_t*, const cuuint32_t*, CUtensorMapInterleave, CUtensorMapSwizzle,
                                  CUtensorMapL2promotion, CUtensorMapFloatOOBfill);

void encode(EncodeTiledFn fn, CUtensorMap* m, const void* ptr, int rows, int cols, int nrow, int nblk, CUtensorMapL2promotion promo) {
    const cuuint64_t dims[3] = {64, (cuuint64_t)rows, (cuuint64_t)cols / 64}, strides[2] = {(cuuint64_t)cols * 2, 128};
    const cuuint32_t box[3] = {64, (cuuint32_t)nrow, (cuuint32_t)nblk}, es[3] = {1, 1, 1};
    fn(m, CU_TENSOR_MAP_DATA_TYPE_BFLOAT16, 3, const_cast<void*>(ptr), dims, strides, box, es,
       CU_TENSOR_MAP_INTERLEAVE_NONE, CU_TENSOR_MAP_SWIZZLE_128B, promo, CU_TENSOR_MAP_FLOAT_OOB_FILL_NONE);
}

}

#define W_PROMO_ 2
#define KV_PROMO_ 3

extern "C" void kernel_launch(void* const* d_in, const int* in_sizes, int n_in, void* d_out, int out_size) {
    (void)in_sizes; (void)n_in; (void)out_size;
    EncodeTiledFn fn = nullptr;
    cudaDriverEntryPointQueryResult qr;
    cudaGetDriverEntryPoint("cuTensorMapEncodeTiled", (void**)&fn, cudaEnableDefault, &qr);
    cudaFuncSetAttribute(fused_decode_kernel, cudaFuncAttributeMaxDynamicSharedMemorySize, SMEM_BYTES);

    int dev = 0, khz = 0, bits = 0;
    cudaGetDevice(&dev);
    cudaDeviceGetAttribute(&khz, cudaDevAttrMemoryClockRate, dev);
    cudaDeviceGetAttribute(&bits, cudaDevAttrGlobalMemoryBusWidth, dev);
    const double rel = (khz > 0 && bits > 0) ? (2619000.0 * 5120.0) / ((double)khz * bits) : 1.0;
    const uint32_t tau = (uint32_t)(TAU_ * rel + 0.5), tau2 = (uint32_t)(TAU2_ * rel + 0.5);

    Maps maps;
    encode(fn, &maps.m[0], d_in[1], NB * HKV * SK, DH, 64, 2, (CUtensorMapL2promotion)KV_PROMO_);
    encode(fn, &maps.m[1], d_in[2], NB * HKV * SK, DH, 64, 2, (CUtensorMapL2promotion)KV_PROMO_);
    encode(fn, &maps.m[2], d_in[3], DM, HQ * DH, 128, 1, (CUtensorMapL2promotion)W_PROMO_);
    encode(fn, &maps.m[3], d_in[4], HQ * DH, DM, 128, 1, (CUtensorMapL2promotion)W_PROMO_);
    encode(fn, &maps.m[4], d_in[6], DM, FF, 32, 4, CU_TENSOR_MAP_L2_PROMOTION_L2_256B);
    encode(fn, &maps.m[5], d_in[8], FF, DM, 16, 8, CU_TENSOR_MAP_L2_PROMOTION_L2_256B);
    fused_decode_kernel<<<N_CTA, THREADS, SMEM_BYTES>>>(maps, (const __nv_bfloat16*)d_in[0], (const __nv_bfloat16*)d_in[7],
                                                        (const __nv_bfloat16*)d_in[9], (__nv_bfloat16*)d_out, d_in[3], tau, tau2);
}
```

```cpp
#include <cuda_runtime.h>
#include <cuda_bf16.h>
#include <cuda.h>
#include <stdint.h>

namespace {

constexpr int NB = 8, DM = 512, HQ = 32, HKV = 8, SK = 4096, DH = 128, FF = 1792;
constexpr int N_ATT = 64, N_FFN = 7, N_CTA = 72;
constexpr int THREADS = 320;
#define D_START_ 4
#define D_MIN_ 4
#define TAU_ 329
#define PACE_OFF_ 36
#define SLIP_ 1
#define D_HI_ 6
constexpr int SLIP = SLIP_, D_HI = D_HI_;
#define WO_GAP_ 16
constexpr int WO_GAP = WO_GAP_;
#define PREF_BYTES_ 16384
#define I_GATE_ 104
constexpr int I_GATE = I_GATE_;
#define D_WO_ 3
constexpr int D_WO = D_WO_;
#define I_FAST_ 92
#define TAU2_ 320
constexpr int I_FAST = I_FAST_;
#define FFN_PACE_ 48
constexpr int STAGES = 12, D_START = D_START_, D_MIN = D_MIN_;
constexpr int PACE_OFF = PACE_OFF_, FFN_PACE = FFN_PACE_;
constexpr int STAGE_BYTES = 16384;
constexpr int KV_TILES = 64;
constexpr int NT_ATT = 4 + 2 * KV_TILES + 4;
constexpr int FS = 256;
constexpr int NT_FFN = 32;
constexpr int XN_STRIDE = DM + 8;
constexpr int H_STRIDE = FS + 8;

constexpr int SM_RING = 0;
constexpr int SM_XN = SM_RING + STAGES * STAGE_BYTES;
constexpr int SM_QIN = SM_XN + NB * XN_STRIDE * 2;
constexpr int SM_ML = SM_QIN + 1024;
constexpr int SM_H = SM_ML + 256;
constexpr int SM_GATE = SM_H + NB * H_STRIDE * 2;
constexpr int SM_BAR = SM_GATE + 4096;
constexpr int SM_END = SM_BAR + (2 * STAGES + 6) * 8;
constexpr int SMEM_BYTES = SM_END + 128;
static_assert(SMEM_BYTES <= 232448, "smem");
static_assert(SM_QIN % 16 == 0 && SM_BAR % 8 == 0, "align");

__device__ float4 g_gp[N_FFN * 8 * 4 * 32];
__device__ unsigned g_ctr;

#define STAMP(k) do {} while (0)

constexpr int SPIN_LIMIT = 1 << 22;

struct Maps { CUtensorMap m[6]; };

__device__ __forceinline__ void mbar_init(uint32_t bar, uint32_t cnt) {
    asm volatile("mbarrier.init.shared::cta.b64 [%0], %1;" ::"r"(bar), "r"(cnt) : "memory");
}
__device__ __forceinline__ void mbar_expect_tx(uint32_t bar, uint32_t bytes) {
    asm volatile("mbarrier.arrive.expect_tx.shared::cta.b64 _, [%0], %1;" ::"r"(bar), "r"(bytes) : "memory");
}
__device__ __forceinline__ void mbar_arrive(uint32_t bar) {
    asm volatile("mbarrier.arrive.shared::cta.b64 _, [%0];" ::"r"(bar) : "memory");
}
__device__ __forceinline__ void mbar_wait(uint32_t bar, uint32_t parity) {
    uint32_t ok;
    int it = 0;
    do {
        asm volatile("{\n.reg .pred p;\nmbarrier.try_wait.parity.shared::cta.b64 p, [%1], %2;\nselp.u32 %0, 1, 0, p;\n}"
                     : "=r"(ok) : "r"(bar), "r"(parity) : "memory");
        if (++it > SPIN_LIMIT) __trap();
    } while (!ok);
}
__device__ __forceinline__ void mbar_wait_cluster(uint32_t bar, uint32_t parity) {
    uint32_t ok;
    int it = 0;
    do {
        asm volatile("{\n.reg .pred p;\nmbarrier.try_wait.parity.relaxed.cluster.shared::cta.b64 p, [%1], %2;\nselp.u32 %0, 1, 0, p;\n}"
                     : "=r"(ok) : "r"(bar), "r"(parity) : "memory");
        if (++it > SPIN_LIMIT) __trap();
    } while (!ok);
    asm volatile("fence.acquire.sync_restrict::shared::cluster.cluster;" ::: "memory");
}
__device__ __forceinline__ bool mbar_test(uint32_t bar, uint32_t parity) {
    uint32_t ok;
    asm volatile("{\n.reg .pred p;\nmbarrier.test_wait.parity.shared::cta.b64 p, [%1], %2;\nselp.u32 %0, 1, 0, p;\n}"
                 : "=r"(ok) : "r"(bar), "r"(parity) : "memory");
    return ok;
}
__device__ __forceinline__ void tma3d(uint32_t dst, const CUtensorMap* m, uint32_t bar, int c1, int c2, uint64_t pol) {
    asm volatile("cp.async.bulk.tensor.3d.shared::cluster.global.mbarrier::complete_tx::bytes.L2::cache_hint [%0], [%1, {%3, %4, %5}], [%2], %6;"
                 ::"r"(dst), "l"(m), "r"(bar), "r"(0), "r"(c1), "r"(c2), "l"(pol) : "memory");
}
__device__ __forceinline__ uint32_t mapa(uint32_t addr, uint32_t rank) {
    uint32_t r;
    asm("mapa.shared::cluster.u32 %0, %1, %2;" : "=r"(r) : "r"(addr), "r"(rank));
    return r;
}
__device__ __forceinline__ void st_async2(uint32_t addr, uint32_t a, uint32_t b, uint32_t bar) {
    asm volatile("st.async.shared::cluster.mbarrier::complete_tx::bytes.v2.b32 [%0], {%1, %2}, [%3];"
                 ::"r"(addr), "r"(a), "r"(b), "r"(bar) : "memory");
}
__device__ __forceinline__ void st_async4(uint32_t addr, const uint4& v, uint32_t bar) {
    asm volatile("st.async.shared::cluster.mbarrier::complete_tx::bytes.v4.b32 [%0], {%1, %2, %3, %4}, [%5];"
                 ::"r"(addr), "r"(v.x), "r"(v.y), "r"(v.z), "r"(v.w), "r"(bar) : "memory");
}
__device__ __forceinline__ void cluster_arrive() { asm volatile("barrier.cluster.arrive.relaxed.aligned;" ::: "memory"); }
__device__ __forceinline__ void cluster_wait() { asm volatile("barrier.cluster.wait.aligned;" ::: "memory"); }
__device__ __forceinline__ void sts32(uint32_t addr, uint32_t v) {
    asm volatile("st.shared.b32 [%0], %1;" ::"r"(addr), "r"(v) : "memory");
}
__device__ __forceinline__ uint4 lds128(uint32_t addr) {
    uint4 v;
    asm volatile("ld.shared.v4.b32 {%0, %1, %2, %3}, [%4];" : "=r"(v.x), "=r"(v.y), "=r"(v.z), "=r"(v.w) : "r"(addr) : "memory");
    return v;
}
__device__ __forceinline__ void ldsm4(uint32_t (&r)[4], uint32_t addr) {
    asm volatile("ldmatrix.sync.aligned.m8n8.x4.shared.b16 {%0, %1, %2, %3}, [%4];"
                 : "=r"(r[0]), "=r"(r[1]), "=r"(r[2]), "=r"(r[3]) : "r"(addr) : "memory");
}
__device__ __forceinline__ void ldsm4t(uint32_t (&r)[4], uint32_t addr) {
    asm volatile("ldmatrix.sync.aligned.m8n8.x4.trans.shared.b16 {%0, %1, %2, %3}, [%4];"
                 : "=r"(r[0]), "=r"(r[1]), "=r"(r[2]), "=r"(r[3]) : "r"(addr) : "memory");
}
__device__ __forceinline__ void mma16816(float (&c)[4], const uint32_t (&a)[4], uint32_t b0, uint32_t b1) {
    asm volatile("mma.sync.aligned.m16n8k16.row.col.f32.bf16.bf16.f32 {%0, %1, %2, %3}, {%4, %5, %6, %7}, {%8, %9}, {%0, %1, %2, %3};"
                 : "+f"(c[0]), "+f"(c[1]), "+f"(c[2]), "+f"(c[3])
                 : "r"(a[0]), "r"(a[1]), "r"(a[2]), "r"(a[3]), "r"(b0), "r"(b1));
}
__device__ __forceinline__ uint32_t movm_t(uint32_t a) {
    uint32_t d;
    asm volatile("movmatrix.sync.aligned.m8n8.trans.b16 %0, %1;" : "=r"(d) : "r"(a));
    return d;
}
__device__ __forceinline__ uint32_t pack_bf16(float lo, float hi) {
    uint32_t d;
    asm("cvt.rn.bf16x2.f32 %0, %1, %2;" : "=r"(d) : "f"(hi), "f"(lo));
    return d;
}
__device__ __forceinline__ float bf_lo(uint32_t v) { return __uint_as_float(v << 16); }
__device__ __forceinline__ float bf_hi(uint32_t v) { return __uint_as_float(v & 0xffff0000u); }
__device__ __forceinline__ float rbf(float x) { return __uint_as_float(pack_bf16(0.f, x)); }
__device__ __forceinline__ uint32_t max_bf16x2(uint32_t a, uint32_t b) {
    uint32_t d;
    asm("max.bf16x2 %0, %1, %2;" : "=r"(d) : "r"(a), "r"(b));
    return d;
}
__device__ __forceinline__ uint32_t sub_bf16x2(uint32_t a, uint32_t b) {
    uint32_t d;
    asm("sub.rn.bf16x2 %0, %1, %2;" : "=r"(d) : "r"(a), "r"(b));
    return d;
}
__device__ __forceinline__ float ex2(float x) {
    float y;
    asm("ex2.approx.ftz.f32 %0, %1;" : "=f"(y) : "f"(x));
    return y;
}
__device__ __forceinline__ float rcp(float x) {
    float y;
    asm("rcp.approx.ftz.f32 %0, %1;" : "=f"(y) : "f"(x));
    return y;
}
__device__ __forceinline__ void red_bf16x2(__nv_bfloat16* p, uint32_t v) {
    asm volatile("red.relaxed.gpu.global.add.noftz.bf16x2 [%0], %1;" ::"l"(p), "r"(v) : "memory");
}
__device__ __forceinline__ bool elect_one() {
    uint32_t p;
    asm volatile("{\n.reg .pred P;\nelect.sync _|P, 0xffffffff;\nselp.u32 %0, 1, 0, P;\n}" : "=r"(p));
    return p;
}
__device__ __forceinline__ uint32_t timer_ns() {
    uint32_t t;
    asm volatile("mov.u32 %0, %%globaltimer_lo;" : "=r"(t));
    return t;
}
__device__ __forceinline__ void bar_compute() { asm volatile("bar.sync 1, 256;" ::: "memory"); }

struct Cursor {
    int slot = 0;
    uint32_t phase = 0;
    __device__ __forceinline__ void adv(int n) { slot += n; if (slot >= STAGES) { slot -= STAGES; phase ^= 1u; } }
};

constexpr float LOG2E = 1.4426950408889634f;

__device__ __forceinline__ void load_w(uint32_t (&a)[8][4], uint32_t addr) {
#pragma unroll
    for (int ks = 0; ks < 8; ks++) ldsm4t(a[ks], addr + ks * 2048);
}
__device__ __forceinline__ void load_act(uint32_t (&b)[4][4], uint32_t addr) {
#pragma unroll
    for (int i = 0; i < 4; i++) ldsm4(b[i], addr + i * 64);
}
__device__ __forceinline__ void mma_stage(float (&acc)[4][4], const uint32_t (&a)[8][4], const uint32_t (&b)[4][4]) {
#pragma unroll
    for (int ks = 0; ks < 8; ks++) mma16816(acc[ks & 3], a[ks], b[ks >> 1][2 * (ks & 1)], b[ks >> 1][2 * (ks & 1) + 1]);
}
__device__ __forceinline__ bool mbar_test_cluster(uint32_t bar) {
    uint32_t ok;
    asm volatile("{\n.reg .pred p;\nmbarrier.test_wait.parity.relaxed.cluster.shared::cta.b64 p, [%1], 0;\nselp.u32 %0, 1, 0, p;\n}"
                 : "=r"(ok) : "r"(bar) : "memory");
    return ok;
}

__global__ void __cluster_dims__(8, 1, 1) __launch_bounds__(THREADS, 1)
fused_decode_kernel(const __grid_constant__ Maps maps, const __nv_bfloat16* __restrict__ x, const __nv_bfloat16* __restrict__ b1,
                    const __nv_bfloat16* __restrict__ b2, __nv_bfloat16* __restrict__ out, const void* wq, const uint32_t tau, const uint32_t tau2,
                    const int shift) {
    extern __shared__ __align__(1024) uint8_t smem_raw[];
    uint32_t sb;
    asm volatile("{\n.reg .u64 a;\ncvta.to.shared.u64 a, %1;\ncvt.u32.u64 %0, a;\n}" : "=r"(sb) : "l"(smem_raw));
    uint8_t* sp = smem_raw;
    const uint32_t bar_full = sb + SM_BAR, bar_empty = bar_full + 8 * STAGES;
    const uint32_t bar_ok = bar_empty + 8 * STAGES, bar_q = bar_ok + 8, bar_o = bar_q + 8, bar_gate = bar_o + 16;

    if (threadIdx.x == 0 && blockIdx.x < N_ATT)
        asm volatile("cp.async.bulk.prefetch.L2.global [%0], %1;"
                     ::"l"(reinterpret_cast<const char*>(wq) + (size_t)blockIdx.x * PREF_BYTES_), "r"(PREF_BYTES_) : "memory");
    const int warp_id = __shfl_sync(0xffffffffu, (int)(threadIdx.x >> 5), 0), lane = threadIdx.x & 31;
    const int cta = (int)blockIdx.x >= shift ? blockIdx.x - shift : blockIdx.x + N_ATT;
    const bool is_att = cta < N_ATT;
    const int hkv = cta >> 3, rank = cta & 7;

    if (warp_id == 0) {
        const bool leader = elect_one();
        if (leader) STAMP(0);
        uint64_t pol;
        asm volatile("createpolicy.fractional.L2::evict_first.b64 %0, 1.0;" : "=l"(pol));
        const int nt = is_att ? NT_ATT : rank < N_FFN ? NT_FFN : 0;
        const int row0 = (rank * HKV + hkv) * SK - 128;
        auto coords = [&](int i, int& mi, int& c1, int& c2) {
            c2 = 0;
            if (is_att) {
                mi = (i >> 1) & 1; c1 = row0 + (i >> 2) * 128 + (i & 1) * 64;
                if (i >= NT_ATT - 12) { mi = (i >> 3) & 1 ^ 1; c1 = row0 + 128 + SK - 256 + (i & 3) * 64; }
                if (i < 4) { mi = 2; c1 = 128 * i; c2 = cta; }
                if (i >= NT_ATT - 4) { mi = 3; c1 = 512 * hkv + 128 * (i - (NT_ATT - 4)); c2 = rank; }
            } else {
                mi = 5; c1 = FS * rank + 16 * (i - 16);
                if (i < 16) { mi = 4; c1 = 32 * i; c2 = 4 * rank; }
            }
        };
#pragma unroll
        for (int i = 0; i < D_START; i++)
            if (leader) mbar_init(bar_full + 8 * i, 1);
        if (nt > 0) {
#pragma unroll
            for (int i = 0; i < D_START; i++) {
                int mi, c1, c2;
                coords(i, mi, c1, c2);
                if (leader) {
                    mbar_expect_tx(bar_full + 8 * i, STAGE_BYTES);
                    tma3d(sb + SM_RING + i * STAGE_BYTES, &maps.m[mi], bar_full + 8 * i, c1, c2, pol);
                }
            }
        }
        const uint32_t t0 = timer_ns();
        __syncthreads();
        if (is_att) cluster_arrive();
        Cursor cur, lag, hi;
        cur.slot = D_START;
        lag.slot = D_START - D_MIN;
        const uint32_t step = is_att ? tau : tau * FFN_PACE / 16;
        uint32_t due = t0 + step * PACE_OFF / 16;
#pragma unroll 1
        for (int i = D_START; i < nt; i++) {
            int mi, c1, c2;
            coords(i, mi, c1, c2);
            const CUtensorMap* map = &maps.m[mi];
            const uint32_t dst = sb + SM_RING + cur.slot * STAGE_BYTES, bar = bar_full + 8 * cur.slot;
            const uint32_t lbar = is_att ? bar_full + 8 * lag.slot : bar_q, lph = is_att ? lag.phase : 0u;
            if (i >= STAGES) mbar_wait(bar + 8 * STAGES, cur.phase ^ 1u);
            if (leader) mbar_expect_tx(bar, STAGE_BYTES);
            int it = 0;
#pragma unroll 1
            while (!mbar_test(lbar, lph) && (int)(timer_ns() - due) < 0 && ++it < 4096) {
            }
            if (leader) tma3d(dst, map, bar, c1, c2, pol);
            if (i == I_GATE && leader) mbar_arrive(bar_gate);
            lag.adv(i == NT_ATT - 5 ? 1 + D_MIN - D_WO : 1);
            cur.adv(1);
            due += i >= I_FAST ? tau2 : step;
            if (i == NT_ATT - 5) due += step * WO_GAP / 16;
            if (i >= D_HI) {
                if (!mbar_test(bar_full + 8 * hi.slot, hi.phase)) due += step * SLIP / 16;
                hi.adv(1);
            }
        }
        if (leader) STAMP(1);
    } else if (warp_id == 1) {
        if (elect_one()) {
            if (sb & 1023u) __trap();
#pragma unroll
            for (int s = D_START; s < STAGES; s++) mbar_init(bar_full + 8 * s, 1);
#pragma unroll
            for (int s = 0; s < STAGES; s++) mbar_init(bar_empty + 8 * s, is_att ? 4 : 8);
            mbar_init(bar_ok, 1);
            mbar_init(bar_q, 1);
            mbar_init(bar_o, 1);
            mbar_init(bar_o + 8, 1);
            mbar_init(bar_gate, 1);
            asm volatile("fence.mbarrier_init.release.cluster;" ::: "memory");
            mbar_expect_tx(bar_q, 1024);
            mbar_expect_tx(bar_o, 7 * 512);
            mbar_expect_tx(bar_o + 8, 7 * 512);
        }
        __syncthreads();
        if (is_att) {
            cluster_arrive();
            mbar_wait(bar_gate, 0);
            if (lane == 0) {
                int it = 0;
                while (true) {
                    unsigned v;
                    asm volatile("ld.acquire.gpu.global.u32 %0, [%1];" : "=r"(v) : "l"(&g_ctr) : "memory");
                    if (v >= 8u) break;
                    __nanosleep(200);
                    if (++it > SPIN_LIMIT) __trap();
                }
            }
            __syncwarp();
            const int g = lane >> 2, t = lane & 3;
#pragma unroll 2
            for (int mt = 0; mt < 4; mt++) {
                const int col = rank * 64 + mt * 16 + g;
                float y[4] = {}, res[4];
#pragma unroll
                for (int i = 0; i < N_FFN; i++) {
                    const float4 v = __ldcg(g_gp + ((i * 8 + rank) * 4 + mt) * 32 + lane);
                    y[0] += v.x; y[1] += v.y; y[2] += v.z; y[3] += v.w;
                }
#pragma unroll
                for (int c = 0; c < 4; c++) {
                    const int cc = col + 8 * (c >> 1), bb = 2 * t + (c & 1);
                    const float z = rbf(rbf(y[c]) + __bfloat162float(b2[cc]));
                    y[c] = rbf(__fdividef(z, 1.0f + __expf(-z)));
                    res[c] = bb == hkv ? __bfloat162float(x[bb * DM + cc]) : 0.f;
                }
                *reinterpret_cast<float4*>(sp + SM_GATE + mt * 1024 + lane * 16) = make_float4(y[0], y[1], y[2], y[3]);
                *reinterpret_cast<float4*>(sp + SM_GATE + mt * 1024 + 512 + lane * 16) = make_float4(res[0], res[1], res[2], res[3]);
            }
            __syncwarp();
            if (lane == 0) {
                mbar_arrive(bar_ok);
                atomicInc(&g_ctr, N_CTA - 1);
                STAMP(8);
            }
        } else if (rank == N_FFN) {
#pragma unroll 4
            for (int i = 0; i < 16; i++) reinterpret_cast<uint4*>(out)[i * 32 + lane] = make_uint4(0, 0, 0, 0);
            __syncwarp();
            if (lane == 0) {
                asm volatile("fence.acq_rel.gpu;" ::: "memory");
                atomicInc(&g_ctr, N_CTA - 1);
            }
        }
    } else {
        const int warp = warp_id - 2, tid = threadIdx.x - 64;
        const int g = lane >> 2, t = lane & 3;
        {
            uint4 xv[2];
#pragma unroll
            for (int i = 0; i < 2; i++) xv[i] = __ldg(reinterpret_cast<const uint4*>(x + warp * DM + i * 256 + lane * 8));
            __syncthreads();
            if (is_att) cluster_arrive();
            uint32_t w[8] = {xv[0].x, xv[0].y, xv[0].z, xv[0].w, xv[1].x, xv[1].y, xv[1].z, xv[1].w};
            float s0 = 0.f, s1 = 0.f;
#pragma unroll
            for (int i = 0; i < 8; i++) { s0 += bf_lo(w[i]); s1 += bf_hi(w[i]); }
            s0 += s1;
#pragma unroll
            for (int o = 16; o > 0; o >>= 1) s0 += __shfl_xor_sync(0xffffffffu, s0, o);
            const float mean = s0 * (1.0f / DM);
            s0 = 0.f; s1 = 0.f;
#pragma unroll
            for (int i = 0; i < 8; i++) {
                const float d0 = bf_lo(w[i]) - mean, d1 = bf_hi(w[i]) - mean;
                s0 += d0 * d0; s1 += d1 * d1;
            }
            s0 += s1;
#pragma unroll
            for (int o = 16; o > 0; o >>= 1) s0 += __shfl_xor_sync(0xffffffffu, s0, o);
            const uint32_t mb = pack_bf16(mean, mean);
            float sd;
            asm("sqrt.approx.f32 %0, %1;" : "=f"(sd) : "f"(rbf(rbf(s0 * (1.0f / DM)) + 1e-5f)));
            const float rs = rcp(rbf(sd));
#pragma unroll
            for (int i = 0; i < 8; i++) {
                const uint32_t d = sub_bf16x2(w[i], mb);
                w[i] = pack_bf16(bf_lo(d) * rs, bf_hi(d) * rs);
            }
#pragma unroll
            for (int i = 0; i < 2; i++)
                *reinterpret_cast<uint4*>(sp + SM_XN + (warp * XN_STRIDE + i * 256 + lane * 8) * 2) =
                    make_uint4(w[4 * i], w[4 * i + 1], w[4 * i + 2], w[4 * i + 3]);
        }
        bar_compute();
        const uint32_t* xn32 = reinterpret_cast<const uint32_t*>(sp + SM_XN) + g * (XN_STRIDE / 2) + t;
        const int krow = (lane & 7) + (lane >> 4) * 8;
        const int cbit = (lane >> 3) & 1;
        const int wq4 = warp & 3;
        Cursor cur;

        if (is_att) {
            cluster_wait();
            const uint32_t wbase = sb + SM_RING + krow * 128 + (((2 * wq4 + cbit) ^ (lane & 7)) << 4);
            const uint32_t abase = sb + SM_XN + (lane & 7) * (XN_STRIDE * 2) + (lane >> 3) * 16;
            if (warp < 4) {
                float acc[4][4] = {};
#pragma unroll 1
                for (int s = 0; s < 4; s++) {
                    uint32_t a[8][4], bf[4][4];
                    load_act(bf, abase + s * 256);
                    mbar_wait(bar_full + 8 * s, 0);
                    load_w(a, wbase + s * STAGE_BYTES);
                    mma_stage(acc, a, bf);
                    __syncwarp();
                    if (lane == 0) mbar_arrive(bar_empty + 8 * s);
                }
                const uint32_t q0 = movm_t(pack_bf16((acc[0][0] + acc[1][0]) + (acc[2][0] + acc[3][0]), (acc[0][1] + acc[1][1]) + (acc[2][1] + acc[3][1])));
                const uint32_t q1 = movm_t(pack_bf16((acc[0][2] + acc[1][2]) + (acc[2][2] + acc[3][2]), (acc[0][3] + acc[1][3]) + (acc[2][3] + acc[3][3])));
                st_async2(mapa(sb + SM_QIN + ((rank * 4 + warp) * 4 + t) * 8, g), q0, q1, mapa(bar_q, g));
            }
            uint2 qf[8];
            mbar_wait_cluster(bar_q, 0);
#pragma unroll
            for (int kk = 0; kk < 8; kk++) qf[kk] = *reinterpret_cast<const uint2*>(sp + SM_QIN + (((g & 3) * 8 + kk) * 4 + t) * 8);
            if (tid == 0) STAMP(3);
            float o[8][4] = {};
            float m0 = -INFINITY, m1 = -INFINITY, l0 = 0.f, l1 = 0.f;
            uint32_t mpk = 0xff80ff80u;
            uint32_t koff[4], voff[4];
#pragma unroll
            for (int i = 0; i < 4; i++) {
                koff[i] = (16 * wq4 + (lane & 7) + cbit * 8) * 128 + (((2 * i + (lane >> 4)) ^ (lane & 7)) << 4);
                voff[i] = (16 * wq4 + krow) * 128 + (((2 * i + cbit) ^ (lane & 7)) << 4);
            }
            uint32_t s01, s23, u01 = 0, u23 = 0;
            cur.adv(4 + (warp >> 2));
#pragma unroll 1
            for (int tile = 0;; tile++) {
                const bool last = tile >= KV_TILES / 2 - 2;
                if (tile == KV_TILES / 2 - 3) mbar_wait(bar_ok, 0);
                const uint32_t kbar = bar_full + 8 * cur.slot, vbar = kbar + 16;
                const uint32_t kb = sb + SM_RING + cur.slot * STAGE_BYTES, vb = kb + 2 * STAGE_BYTES;
                uint32_t a[8][4];
                mbar_wait(kbar, cur.phase);
#pragma unroll
                for (int i = 0; i < 8; i++) ldsm4(a[i], kb + (i >> 2) * 8192 + koff[i & 3]);
                const bool early = !last && mbar_test(vbar, cur.phase);
                float sa[4][4] = {};
#pragma unroll
                for (int i = 0; i < 8; i++) mma16816(sa[i & 3], a[i], qf[i].x, qf[i].y);
                __syncwarp();
                if (lane == 0) mbar_arrive(kbar + 8 * STAGES);
                if (early) {
#pragma unroll
                    for (int i = 0; i < 8; i++) ldsm4t(a[i], vb + (i >> 2) * 8192 + voff[i & 3]);
                }
                s01 = pack_bf16((sa[0][0] + sa[1][0]) + (sa[2][0] + sa[3][0]), (sa[0][1] + sa[1][1]) + (sa[2][1] + sa[3][1]));
                s23 = pack_bf16((sa[0][2] + sa[1][2]) + (sa[2][2] + sa[3][2]), (sa[0][3] + sa[1][3]) + (sa[2][3] + sa[3][3]));
                const float scale = 0.08838834764831845f;
                s01 = pack_bf16(bf_lo(s01) * scale, bf_hi(s01) * scale);
                s23 = pack_bf16(bf_lo(s23) * scale, bf_hi(s23) * scale);
                if (last) {
                    if (tile == KV_TILES / 2 - 1) break;
                    u01 = s01; u23 = s23;
                    cur.adv(2);
                    continue;
                }
                uint32_t mx = max_bf16x2(max_bf16x2(s01, s23), mpk);
                if (__any_sync(0xffffffffu, mx != mpk)) {
                    mx = max_bf16x2(mx, __shfl_xor_sync(0xffffffffu, mx, 4));
                    mx = max_bf16x2(mx, __shfl_xor_sync(0xffffffffu, mx, 8));
                    mx = max_bf16x2(mx, __shfl_xor_sync(0xffffffffu, mx, 16));
                    const float n0 = bf_lo(mx), n1 = bf_hi(mx);
                    const float a0 = ex2((m0 - n0) * LOG2E), a1 = ex2((m1 - n1) * LOG2E);
                    m0 = n0; m1 = n1; mpk = mx;
                    l0 *= a0; l1 *= a1;
#pragma unroll
                    for (int mt = 0; mt < 8; mt++) { o[mt][0] *= a0; o[mt][1] *= a1; o[mt][2] *= a0; o[mt][3] *= a1; }
                }
                const float p0 = ex2((bf_lo(s01) - m0) * LOG2E), p1 = ex2((bf_hi(s01) - m1) * LOG2E);
                const float p2 = ex2((bf_lo(s23) - m0) * LOG2E), p3 = ex2((bf_hi(s23) - m1) * LOG2E);
                l0 += p0 + p2; l1 += p1 + p3;
                const uint32_t pb0 = movm_t(pack_bf16(p0, p1)), pb1 = movm_t(pack_bf16(p2, p3));
                if (!early) {
                    mbar_wait(vbar, cur.phase);
#pragma unroll
                    for (int i = 0; i < 8; i++) ldsm4t(a[i], vb + (i >> 2) * 8192 + voff[i & 3]);
                }
#pragma unroll
                for (int i = 0; i < 8; i++) mma16816(o[i], a[i], pb0, pb1);
                __syncwarp();
                if (lane == 0) mbar_arrive(vbar + 8 * STAGES);
                cur.adv(4);
            }
            constexpr int SLOT_K = (NT_ATT - 12) % STAGES, SLOT_V = SLOT_K + 4;
            static_assert(SLOT_V + 4 <= STAGES, "last tiles must not wrap");
            constexpr uint32_t PH_LAST = ((NT_ATT - 12) / STAGES) & 1;
            const uint32_t orow = sb + SM_XN + rank * (XN_STRIDE * 2);
            const bool hi = t >= 2;
            {
                uint32_t mx = max_bf16x2(max_bf16x2(max_bf16x2(s01, s23), max_bf16x2(u01, u23)), mpk);
                mx = max_bf16x2(mx, __shfl_xor_sync(0xffffffffu, mx, 4));
                mx = max_bf16x2(mx, __shfl_xor_sync(0xffffffffu, mx, 8));
                mx = max_bf16x2(mx, __shfl_xor_sync(0xffffffffu, mx, 16));
                if (lane < 2) sts32(sb + SM_ML + lane * 32 + warp * 4, mx);
                bar_compute();
                const uint4 ma = lds128(sb + SM_ML + (t & 1) * 32), mb = lds128(sb + SM_ML + (t & 1) * 32 + 16);
                const uint32_t M = max_bf16x2(max_bf16x2(max_bf16x2(ma.x, ma.y), max_bf16x2(ma.z, ma.w)),
                                              max_bf16x2(max_bf16x2(mb.x, mb.y), max_bf16x2(mb.z, mb.w)));
                const float M0 = bf_lo(M), M1 = bf_hi(M);
                const float f0 = ex2((m0 - M0) * LOG2E), f1 = ex2((m1 - M1) * LOG2E);
                l0 *= f0; l1 *= f1;
#pragma unroll
                for (int j = 0; j < 2; j++) {
                    const uint32_t a01 = j ? s01 : u01, a23 = j ? s23 : u23;
                    const float p0 = ex2((bf_lo(a01) - M0) * LOG2E), p1 = ex2((bf_hi(a01) - M1) * LOG2E);
                    const float p2 = ex2((bf_lo(a23) - M0) * LOG2E), p3 = ex2((bf_hi(a23) - M1) * LOG2E);
                    l0 += p0 + p2; l1 += p1 + p3;
                    const uint32_t pb0 = movm_t(pack_bf16(p0, p1)), pb1 = movm_t(pack_bf16(p2, p3));
                    if (lane < 16) *reinterpret_cast<uint2*>(sp + SM_H + lane * 144 + (warp >> 2) * 64 + j * 32 + wq4 * 8) = make_uint2(pb0, pb1);
                }
                uint8_t* part = sp + SM_RING + (SLOT_K + (warp >> 2)) * STAGE_BYTES + wq4 * 2048 + (t >> 1) * 1024 +
                                ((2 * g + (t & 1)) ^ (4 * ((t >> 1) ^ (warp >> 2)))) * 16;
#pragma unroll
                for (int i = 0; i < 4; i++)
                    *reinterpret_cast<float4*>(part + i * 256) =
                        make_float4((hi ? o[4 + i][0] : o[i][0]) * f0, (hi ? o[4 + i][1] : o[i][1]) * f1,
                                    (hi ? o[4 + i][2] : o[i][2]) * f0, (hi ? o[4 + i][3] : o[i][3]) * f1);
#pragma unroll
                for (int of = 4; of < 32; of <<= 1) {
                    l0 += __shfl_xor_sync(0xffffffffu, l0, of);
                    l1 += __shfl_xor_sync(0xffffffffu, l1, of);
                }
                if (lane < 2) *reinterpret_cast<float2*>(sp + SM_ML + 64 + lane * 64 + warp * 8) = make_float2(l0, l1);
            }
            bar_compute();
            {
                uint4 pf[4];
#pragma unroll
                for (int i = 0; i < 4; i++) pf[i] = *reinterpret_cast<const uint4*>(sp + SM_H + (lane & 15) * 144 + (lane >> 4) * 64 + i * 16);
                const uint8_t* psum = sp + SM_RING + (SLOT_K + (t >> 1)) * STAGE_BYTES + warp * 256 +
                                      ((2 * g + (t & 1)) ^ (4 * ((t >> 1) ^ (warp >> 2)))) * 16;
                float acc[4][4];
#pragma unroll
                for (int w = 0; w < 4; w++) {
                    const float4 v = *reinterpret_cast<const float4*>(psum + w * 2048);
                    acc[w][0] = v.x; acc[w][1] = v.y; acc[w][2] = v.z; acc[w][3] = v.w;
                }
                float L0 = 0.f, L1 = 0.f;
#pragma unroll
                for (int i = 0; i < 4; i++) {
                    const float4 v = *reinterpret_cast<const float4*>(sp + SM_ML + 64 + (t & 1) * 64 + i * 16);
                    L0 += v.x + v.z; L1 += v.y + v.w;
                }
                const float i0 = rcp(L0), i1 = rcp(L1);
                const uint32_t vbase = wbase + SLOT_V * STAGE_BYTES + (warp >> 2) * 8192;
                const uint32_t ost = orow + (g & 3) * 256 + warp * 32 + (g >> 2) * 16 + t * 4;
#pragma unroll
                for (int j = 0; j < 4; j++) {
                    uint32_t a[4][4];
                    const bool on = (lane >> 4) == (j & 1);
                    const uint4 pa = pf[j & 2], pb = pf[(j & 2) + 1];
                    mbar_wait(bar_full + 8 * (SLOT_V + j), PH_LAST);
#pragma unroll
                    for (int ks = 0; ks < 4; ks++) ldsm4t(a[ks], vbase + j * STAGE_BYTES + ks * 2048);
                    mma16816(acc[0], a[0], on ? pa.x : 0u, on ? pa.y : 0u);
                    mma16816(acc[1], a[1], on ? pa.z : 0u, on ? pa.w : 0u);
                    mma16816(acc[2], a[2], on ? pb.x : 0u, on ? pb.y : 0u);
                    mma16816(acc[3], a[3], on ? pb.z : 0u, on ? pb.w : 0u);
                }
#pragma unroll
                for (int c = 0; c < 4; c++) { acc[0][c] += acc[2][c]; acc[1][c] += acc[3][c]; }
                const float c0 = acc[0][0] + acc[1][0], c1 = acc[0][1] + acc[1][1], c2 = acc[0][2] + acc[1][2], c3 = acc[0][3] + acc[1][3];
                const float r0 = (hi ? c2 : c0) + __shfl_xor_sync(0xffffffffu, hi ? c0 : c2, 2);
                const float r1 = (hi ? c3 : c1) + __shfl_xor_sync(0xffffffffu, hi ? c1 : c3, 2);
                sts32(ost, movm_t(pack_bf16(r0 * i0, r1 * i1)));
            }
            if (tid == 0) STAMP(5);
            bar_compute();
            if (warp != rank) {
                const uint4 u0 = lds128(orow + lane * 16), u1 = lds128(orow + lane * 16 + 512);
                const uint32_t odst = mapa(orow + lane * 16, warp), obar = mapa(bar_o, warp);
                st_async4(odst, u0, obar);
                st_async4(odst + 512, u1, obar + 8);
            }
            if (tid == 0) STAMP(6);
            if (warp < 4) {
                __nv_bfloat16* dst = out + g * DM + rank * 64 + warp * 16 + 2 * t;
                constexpr uint32_t ph = ((NT_ATT - 4) / STAGES) & 1;
                static_assert((NT_ATT - 4) % STAGES == 0, "wo must start in slot 0");
                uint32_t a[4][8][4], bf[4][4][4];
                float acc[4][4] = {};
                const bool w01 = mbar_test(bar_full, ph) & mbar_test(bar_full + 8, ph);
                const bool o01 = mbar_test_cluster(bar_o) & mbar_test_cluster(bar_o + 8);
                if (!w01) mbar_wait(bar_full, ph);
                load_w(a[0], wbase);
                if (!w01) mbar_wait(bar_full + 8, ph);
                load_w(a[1], wbase + STAGE_BYTES);
                if (!o01) mbar_wait_cluster(bar_o, 0);
                asm volatile("fence.acquire.sync_restrict::shared::cluster.cluster;" ::: "memory");
                load_act(bf[0], abase);
                load_act(bf[1], abase + 256);
                if (!o01) mbar_wait_cluster(bar_o + 8, 0);
                const bool w2 = mbar_test(bar_full + 16, ph), w3 = mbar_test(bar_full + 24, ph);
                load_act(bf[2], abase + 512);
                load_act(bf[3], abase + 768);
                mma_stage(acc, a[0], bf[0]);
                if (w2) load_w(a[2], wbase + 2 * STAGE_BYTES);
                mma_stage(acc, a[1], bf[1]);
                if (!w2) { mbar_wait(bar_full + 16, ph); load_w(a[2], wbase + 2 * STAGE_BYTES); }
                if (w3) load_w(a[3], wbase + 3 * STAGE_BYTES);
                mma_stage(acc, a[2], bf[2]);
                if (!w3) { mbar_wait(bar_full + 24, ph); load_w(a[3], wbase + 3 * STAGE_BYTES); }
                mma_stage(acc, a[3], bf[3]);
                float r[4];
                const uint4 gt = lds128(sb + SM_GATE + warp * 1024 + lane * 16), rs = lds128(sb + SM_GATE + warp * 1024 + 512 + lane * 16);
#pragma unroll
                for (int c = 0; c < 4; c++) r[c] = (acc[0][c] + acc[1][c]) + (acc[2][c] + acc[3][c]);
                red_bf16x2(dst, movm_t(pack_bf16(fmaf(r[0], __uint_as_float(gt.x), __uint_as_float(rs.x)),
                                                 fmaf(r[1], __uint_as_float(gt.y), __uint_as_float(rs.y)))));
                red_bf16x2(dst + 8, movm_t(pack_bf16(fmaf(r[2], __uint_as_float(gt.z), __uint_as_float(rs.z)),
                                                     fmaf(r[3], __uint_as_float(gt.w), __uint_as_float(rs.w)))));
                if (tid == 0) STAMP(7);
            }
        } else if (rank < N_FFN) {
            if (tid < FS / 8) *reinterpret_cast<uint4*>(sp + SM_QIN + tid * 16) = __ldg(reinterpret_cast<const uint4*>(b1 + FS * rank) + tid);
            float acc[4][4] = {};
#pragma unroll 1
            for (int kt = 0; kt < 16; kt++) {
                mbar_wait(bar_full + 8 * cur.slot, cur.phase);
                const uint32_t base = sb + SM_RING + cur.slot * STAGE_BYTES + (warp >> 1) * 4096 + krow * 128;
#pragma unroll
                for (int ks = 0; ks < 2; ks++) {
                    const uint32_t b0 = xn32[kt * 16 + ks * 8], b1r = xn32[kt * 16 + ks * 8 + 4];
#pragma unroll
                    for (int mt = 0; mt < 2; mt++) {
                        uint32_t a[4];
                        ldsm4t(a, base + ks * 2048 + (((4 * (warp & 1) + 2 * mt + cbit) ^ (lane & 7)) << 4));
                        mma16816(acc[mt], a, b0, b1r);
                    }
                }
                __syncwarp();
                if (lane == 0) mbar_arrive(bar_empty + 8 * cur.slot);
                cur.adv(1);
            }
            bar_compute();
            __nv_bfloat16* hs = reinterpret_cast<__nv_bfloat16*>(sp + SM_H);
            const __nv_bfloat16* b1s = reinterpret_cast<const __nv_bfloat16*>(sp + SM_QIN);
#pragma unroll
            for (int mt = 0; mt < 2; mt++)
#pragma unroll
                for (int c = 0; c < 4; c++) {
                    const int u = warp * 32 + mt * 16 + g + (c >> 1) * 8;
                    const float hv = rbf(rbf(acc[mt][c]) + __bfloat162float(b1s[u]));
                    const float inner = 0.7978845608028654f * (hv + 0.044715f * hv * hv * hv);
                    hs[(2 * t + (c & 1)) * H_STRIDE + u] = __float2bfloat16_rn(0.5f * hv * (1.0f + tanhf(inner)));
                    acc[mt][c] = 0.f;
                }
            bar_compute();
            const uint32_t* h32 = reinterpret_cast<const uint32_t*>(sp + SM_H) + g * (H_STRIDE / 2) + t;
#pragma unroll 1
            for (int kt = 0; kt < 16; kt++) {
                const uint32_t b0 = h32[kt * 8], b1r = h32[kt * 8 + 4];
                mbar_wait(bar_full + 8 * cur.slot, cur.phase);
                const uint32_t base = sb + SM_RING + cur.slot * STAGE_BYTES + warp * 2048 + krow * 128;
#pragma unroll
                for (int mt = 0; mt < 4; mt++) {
                    uint32_t a[4];
                    ldsm4t(a, base + (((2 * mt + cbit) ^ (lane & 7)) << 4));
                    mma16816(acc[mt], a, b0, b1r);
                }
                __syncwarp();
                if (lane == 0) mbar_arrive(bar_empty + 8 * cur.slot);
                cur.adv(1);
            }
#pragma unroll
            for (int mt = 0; mt < 4; mt++)
                g_gp[((rank * 8 + warp) * 4 + mt) * 32 + lane] = make_float4(acc[mt][0], acc[mt][1], acc[mt][2], acc[mt][3]);
            bar_compute();
            if (tid == 0) {
                asm volatile("fence.acq_rel.gpu;" ::: "memory");
                atomicInc(&g_ctr, N_CTA - 1);
            }
            if (tid == 0) STAMP(7);
        }
    }
}

typedef CUresult (*EncodeTiledFn)(CUtensorMap*, CUtensorMapDataType, cuuint32_t, void*, const cuuint64_t*, const cuuint64_t*,
                                  const cuuint32_t*, const cuuint32_t*, CUtensorMapInterleave, CUtensorMapSwizzle,
                                  CUtensorMapL2promotion, CUtensorMapFloatOOBfill);

void encode(EncodeTiledFn fn, CUtensorMap* m, const void* ptr, int rows, int cols, int nrow, int nblk, CUtensorMapL2promotion promo) {
    const cuuint64_t dims[3] = {64, (cuuint64_t)rows, (cuuint64_t)cols / 64}, strides[2] = {(cuuint64_t)cols * 2, 128};
    const cuuint32_t box[3] = {64, (cuuint32_t)nrow, (cuuint32_t)nblk}, es[3] = {1, 1, 1};
    fn(m, CU_TENSOR_MAP_DATA_TYPE_BFLOAT16, 3, const_cast<void*>(ptr), dims, strides, box, es,
       CU_TENSOR_MAP_INTERLEAVE_NONE, CU_TENSOR_MAP_SWIZZLE_128B, promo, CU_TENSOR_MAP_FLOAT_OOB_FILL_NONE);
}

}

#define W_PROMO_ 2
#define KV_PROMO_ 3

extern "C" void kernel_launch(void* const* d_in, const int* in_sizes, int n_in, void* d_out, int out_size) {
    (void)in_sizes; (void)n_in; (void)out_size;
    EncodeTiledFn fn = nullptr;
    cudaDriverEntryPointQueryResult qr;
    cudaGetDriverEntryPoint("cuTensorMapEncodeTiled", (void**)&fn, cudaEnableDefault, &qr);
    cudaFuncSetAttribute(fused_decode_kernel, cudaFuncAttributeMaxDynamicSharedMemorySize, SMEM_BYTES);

    int dev = 0, khz = 0, bits = 0;
    cudaGetDevice(&dev);
    cudaDeviceGetAttribute(&khz, cudaDevAttrMemoryClockRate, dev);
    cudaDeviceGetAttribute(&bits, cudaDevAttrGlobalMemoryBusWidth, dev);
    const double rel = (khz > 0 && bits > 0) ? (2619000.0 * 5120.0) / ((double)khz * bits) : 1.0;
    const uint32_t tau = (uint32_t)(TAU_ * rel + 0.5), tau2 = (uint32_t)(TAU2_ * rel + 0.5);

    int nclusters = 0;
    {
        cudaLaunchConfig_t cfg = {};
        cfg.gridDim = dim3(N_CTA); cfg.blockDim = dim3(THREADS); cfg.dynamicSmemBytes = SMEM_BYTES;
        cudaLaunchAttribute at;
        at.id = cudaLaunchAttributeClusterDimension;
        at.val.clusterDim.x = 8; at.val.clusterDim.y = 1; at.val.clusterDim.z = 1;
        cfg.attrs = &at; cfg.numAttrs = 1;
        if (cudaOccupancyMaxActiveClusters(&nclusters, fused_decode_kernel, &cfg) != cudaSuccess) { nclusters = 0; cudaGetLastError(); }
    }
    const int shift = nclusters >= N_CTA / 8 ? 0 : 8;

    Maps maps;
    encode(fn, &maps.m[0], d_in[1], NB * HKV * SK, DH, 64, 2, (CUtensorMapL2promotion)KV_PROMO_);
    encode(fn, &maps.m[1], d_in[2], NB * HKV * SK, DH, 64, 2, (CUtensorMapL2promotion)KV_PROMO_);
    encode(fn, &maps.m[2], d_in[3], DM, HQ * DH, 128, 1, (CUtensorMapL2promotion)W_PROMO_);
    encode(fn, &maps.m[3], d_in[4], HQ * DH, DM, 128, 1, (CUtensorMapL2promotion)W_PROMO_);
    encode(fn, &maps.m[4], d_in[6], DM, FF, 32, 4, CU_TENSOR_MAP_L2_PROMOTION_L2_256B);
    encode(fn, &maps.m[5], d_in[8], FF, DM, 16, 8, CU_TENSOR_MAP_L2_PROMOTION_L2_256B);
    fused_decode_kernel<<<N_CTA, THREADS, SMEM_BYTES>>>(maps, (const __nv_bfloat16*)d_in[0], (const __nv_bfloat16*)d_in[7],
                                                        (const __nv_bfloat16*)d_in[9], (__nv_bfloat16*)d_out, d_in[3], tau, tau2, shift);
}
```

```cpp
#include <cuda_runtime.h>
#include <cuda_bf16.h>
#include <cuda.h>
#include <stdint.h>

namespace {

constexpr int NB = 8, DM = 512, HQ = 32, HKV = 8, SK = 4096, DH = 128, FF = 1792;
constexpr int N_ATT = 64, N_FFN = 7, N_CTA = 72;
constexpr int THREADS = 320;
constexpr int STAGES = 12;
constexpr int TAU_NS = 329, TAU2_NS = 320;
constexpr int I_FAST = 92;
constexpr int D_START = 4;
constexpr int PACE_OFF = 36;
constexpr int D_MIN = 4, D_WO = 3;
constexpr int D_HI = 6, SLIP = 1;
constexpr int WO_GAP = 16;
constexpr int FFN_PACE = 48;
constexpr int I_GATE = 104;
constexpr int PREF_BYTES = 16384;
constexpr int STAGE_BYTES = 16384;
constexpr int KV_TILES = 64;
constexpr int NT_ATT = 4 + 2 * KV_TILES + 4;
constexpr int FS = 256;
constexpr int NT_FFN = 32;
constexpr int XN_STRIDE = DM + 8;
constexpr int H_STRIDE = FS + 8;

constexpr int SM_RING = 0;
constexpr int SM_XN = SM_RING + STAGES * STAGE_BYTES;
constexpr int SM_QIN = SM_XN + NB * XN_STRIDE * 2;
constexpr int SM_ML = SM_QIN + 1024;
constexpr int SM_H = SM_ML + 256;
constexpr int SM_GATE = SM_H + NB * H_STRIDE * 2;
constexpr int SM_BAR = SM_GATE + 4096;
constexpr int SM_END = SM_BAR + (2 * STAGES + 6) * 8;
constexpr int SMEM_BYTES = SM_END + 128;
static_assert(SMEM_BYTES <= 232448, "smem");
static_assert(SM_QIN % 16 == 0 && SM_BAR % 8 == 0, "align");

__device__ float4 g_gp[N_FFN * 8 * 4 * 32];
__device__ unsigned g_ctr;


constexpr int SPIN_LIMIT = 1 << 22;

struct Maps { CUtensorMap m[6]; };

__device__ __forceinline__ void mbar_init(uint32_t bar, uint32_t cnt) {
    asm volatile("mbarrier.init.shared::cta.b64 [%0], %1;" ::"r"(bar), "r"(cnt) : "memory");
}
__device__ __forceinline__ void mbar_expect_tx(uint32_t bar, uint32_t bytes) {
    asm volatile("mbarrier.arrive.expect_tx.shared::cta.b64 _, [%0], %1;" ::"r"(bar), "r"(bytes) : "memory");
}
__device__ __forceinline__ void mbar_arrive(uint32_t bar) {
    asm volatile("mbarrier.arrive.shared::cta.b64 _, [%0];" ::"r"(bar) : "memory");
}
__device__ __forceinline__ void mbar_wait(uint32_t bar, uint32_t parity) {
    uint32_t ok;
    int it = 0;
    do {
        asm volatile("{\n.reg .pred p;\nmbarrier.try_wait.parity.shared::cta.b64 p, [%1], %2;\nselp.u32 %0, 1, 0, p;\n}"
                     : "=r"(ok) : "r"(bar), "r"(parity) : "memory");
        if (++it > SPIN_LIMIT) __trap();
    } while (!ok);
}
__device__ __forceinline__ void mbar_wait_cluster(uint32_t bar, uint32_t parity) {
    uint32_t ok;
    int it = 0;
    do {
        asm volatile("{\n.reg .pred p;\nmbarrier.try_wait.parity.relaxed.cluster.shared::cta.b64 p, [%1], %2;\nselp.u32 %0, 1, 0, p;\n}"
                     : "=r"(ok) : "r"(bar), "r"(parity) : "memory");
        if (++it > SPIN_LIMIT) __trap();
    } while (!ok);
    asm volatile("fence.acquire.sync_restrict::shared::cluster.cluster;" ::: "memory");
}
__device__ __forceinline__ bool mbar_test(uint32_t bar, uint32_t parity) {
    uint32_t ok;
    asm volatile("{\n.reg .pred p;\nmbarrier.test_wait.parity.shared::cta.b64 p, [%1], %2;\nselp.u32 %0, 1, 0, p;\n}"
                 : "=r"(ok) : "r"(bar), "r"(parity) : "memory");
    return ok;
}
__device__ __forceinline__ void tma3d(uint32_t dst, const CUtensorMap* m, uint32_t bar, int c1, int c2, uint64_t pol) {
    asm volatile("cp.async.bulk.tensor.3d.shared::cluster.global.mbarrier::complete_tx::bytes.L2::cache_hint [%0], [%1, {%3, %4, %5}], [%2], %6;"
                 ::"r"(dst), "l"(m), "r"(bar), "r"(0), "r"(c1), "r"(c2), "l"(pol) : "memory");
}
__device__ __forceinline__ uint32_t mapa(uint32_t addr, uint32_t rank) {
    uint32_t r;
    asm("mapa.shared::cluster.u32 %0, %1, %2;" : "=r"(r) : "r"(addr), "r"(rank));
    return r;
}
__device__ __forceinline__ void st_async2(uint32_t addr, uint32_t a, uint32_t b, uint32_t bar) {
    asm volatile("st.async.shared::cluster.mbarrier::complete_tx::bytes.v2.b32 [%0], {%1, %2}, [%3];"
                 ::"r"(addr), "r"(a), "r"(b), "r"(bar) : "memory");
}
__device__ __forceinline__ void st_async4(uint32_t addr, const uint4& v, uint32_t bar) {
    asm volatile("st.async.shared::cluster.mbarrier::complete_tx::bytes.v4.b32 [%0], {%1, %2, %3, %4}, [%5];"
                 ::"r"(addr), "r"(v.x), "r"(v.y), "r"(v.z), "r"(v.w), "r"(bar) : "memory");
}
__device__ __forceinline__ void cluster_arrive() { asm volatile("barrier.cluster.arrive.relaxed.aligned;" ::: "memory"); }
__device__ __forceinline__ void cluster_wait() { asm volatile("barrier.cluster.wait.aligned;" ::: "memory"); }
__device__ __forceinline__ void sts32(uint32_t addr, uint32_t v) {
    asm volatile("st.shared.b32 [%0], %1;" ::"r"(addr), "r"(v) : "memory");
}
__device__ __forceinline__ uint4 lds128(uint32_t addr) {
    uint4 v;
    asm volatile("ld.shared.v4.b32 {%0, %1, %2, %3}, [%4];" : "=r"(v.x), "=r"(v.y), "=r"(v.z), "=r"(v.w) : "r"(addr) : "memory");
    return v;
}
__device__ __forceinline__ void ldsm4(uint32_t (&r)[4], uint32_t addr) {
    asm volatile("ldmatrix.sync.aligned.m8n8.x4.shared.b16 {%0, %1, %2, %3}, [%4];"
                 : "=r"(r[0]), "=r"(r[1]), "=r"(r[2]), "=r"(r[3]) : "r"(addr) : "memory");
}
__device__ __forceinline__ void ldsm4t(uint32_t (&r)[4], uint32_t addr) {
    asm volatile("ldmatrix.sync.aligned.m8n8.x4.trans.shared.b16 {%0, %1, %2, %3}, [%4];"
                 : "=r"(r[0]), "=r"(r[1]), "=r"(r[2]), "=r"(r[3]) : "r"(addr) : "memory");
}
__device__ __forceinline__ void mma16816(float (&c)[4], const uint32_t (&a)[4], uint32_t b0, uint32_t b1) {
    asm volatile("mma.sync.aligned.m16n8k16.row.col.f32.bf16.bf16.f32 {%0, %1, %2, %3}, {%4, %5, %6, %7}, {%8, %9}, {%0, %1, %2, %3};"
                 : "+f"(c[0]), "+f"(c[1]), "+f"(c[2]), "+f"(c[3])
                 : "r"(a[0]), "r"(a[1]), "r"(a[2]), "r"(a[3]), "r"(b0), "r"(b1));
}
__device__ __forceinline__ uint32_t movm_t(uint32_t a) {
    uint32_t d;
    asm volatile("movmatrix.sync.aligned.m8n8.trans.b16 %0, %1;" : "=r"(d) : "r"(a));
    return d;
}
__device__ __forceinline__ uint32_t pack_bf16(float lo, float hi) {
    uint32_t d;
    asm("cvt.rn.bf16x2.f32 %0, %1, %2;" : "=r"(d) : "f"(hi), "f"(lo));
    return d;
}
__device__ __forceinline__ float bf_lo(uint32_t v) { return __uint_as_float(v << 16); }
__device__ __forceinline__ float bf_hi(uint32_t v) { return __uint_as_float(v & 0xffff0000u); }
__device__ __forceinline__ float rbf(float x) { return __uint_as_float(pack_bf16(0.f, x)); }
__device__ __forceinline__ uint32_t max_bf16x2(uint32_t a, uint32_t b) {
    uint32_t d;
    asm("max.bf16x2 %0, %1, %2;" : "=r"(d) : "r"(a), "r"(b));
    return d;
}
__device__ __forceinline__ uint32_t sub_bf16x2(uint32_t a, uint32_t b) {
    uint32_t d;
    asm("sub.rn.bf16x2 %0, %1, %2;" : "=r"(d) : "r"(a), "r"(b));
    return d;
}
__device__ __forceinline__ float ex2(float x) {
    float y;
    asm("ex2.approx.ftz.f32 %0, %1;" : "=f"(y) : "f"(x));
    return y;
}
__device__ __forceinline__ float rcp(float x) {
    float y;
    asm("rcp.approx.ftz.f32 %0, %1;" : "=f"(y) : "f"(x));
    return y;
}
__device__ __forceinline__ void red_bf16x2(__nv_bfloat16* p, uint32_t v) {
    asm volatile("red.relaxed.gpu.global.add.noftz.bf16x2 [%0], %1;" ::"l"(p), "r"(v) : "memory");
}
__device__ __forceinline__ bool elect_one() {
    uint32_t p;
    asm volatile("{\n.reg .pred P;\nelect.sync _|P, 0xffffffff;\nselp.u32 %0, 1, 0, P;\n}" : "=r"(p));
    return p;
}
__device__ __forceinline__ uint32_t timer_ns() {
    uint32_t t;
    asm volatile("mov.u32 %0, %%globaltimer_lo;" : "=r"(t));
    return t;
}
__device__ __forceinline__ void bar_compute() { asm volatile("bar.sync 1, 256;" ::: "memory"); }

struct Cursor {
    int slot = 0;
    uint32_t phase = 0;
    __device__ __forceinline__ void adv(int n) { slot += n; if (slot >= STAGES) { slot -= STAGES; phase ^= 1u; } }
};

constexpr float LOG2E = 1.4426950408889634f;

__device__ __forceinline__ void load_w(uint32_t (&a)[8][4], uint32_t addr) {
#pragma unroll
    for (int ks = 0; ks < 8; ks++) ldsm4t(a[ks], addr + ks * 2048);
}
__device__ __forceinline__ void load_act(uint32_t (&b)[4][4], uint32_t addr) {
#pragma unroll
    for (int i = 0; i < 4; i++) ldsm4(b[i], addr + i * 64);
}
__device__ __forceinline__ void mma_stage(float (&acc)[4][4], const uint32_t (&a)[8][4], const uint32_t (&b)[4][4]) {
#pragma unroll
    for (int ks = 0; ks < 8; ks++) mma16816(acc[ks & 3], a[ks], b[ks >> 1][2 * (ks & 1)], b[ks >> 1][2 * (ks & 1) + 1]);
}
__device__ __forceinline__ bool mbar_test_cluster(uint32_t bar) {
    uint32_t ok;
    asm volatile("{\n.reg .pred p;\nmbarrier.test_wait.parity.relaxed.cluster.shared::cta.b64 p, [%1], 0;\nselp.u32 %0, 1, 0, p;\n}"
                 : "=r"(ok) : "r"(bar) : "memory");
    return ok;
}

__global__ void __cluster_dims__(8, 1, 1) __launch_bounds__(THREADS, 1)
fused_decode_kernel(const __grid_constant__ Maps maps, const __nv_bfloat16* __restrict__ x, const __nv_bfloat16* __restrict__ b1,
                    const __nv_bfloat16* __restrict__ b2, __nv_bfloat16* __restrict__ out, const void* wq, const uint32_t tau, const uint32_t tau2,
                    const int shift) {
    extern __shared__ __align__(1024) uint8_t smem_raw[];
    uint32_t sb;
    asm volatile("{\n.reg .u64 a;\ncvta.to.shared.u64 a, %1;\ncvt.u32.u64 %0, a;\n}" : "=r"(sb) : "l"(smem_raw));
    uint8_t* sp = smem_raw;
    const uint32_t bar_full = sb + SM_BAR, bar_empty = bar_full + 8 * STAGES;
    const uint32_t bar_ok = bar_empty + 8 * STAGES, bar_q = bar_ok + 8, bar_o = bar_q + 8, bar_gate = bar_o + 16;

    if (threadIdx.x == 0 && blockIdx.x < N_ATT)
        asm volatile("cp.async.bulk.prefetch.L2.global [%0], %1;"
                     ::"l"(reinterpret_cast<const char*>(wq) + (size_t)blockIdx.x * PREF_BYTES), "r"(PREF_BYTES) : "memory");
    const int warp_id = __shfl_sync(0xffffffffu, (int)(threadIdx.x >> 5), 0), lane = threadIdx.x & 31;
    const int cta = (int)blockIdx.x >= shift ? blockIdx.x - shift : blockIdx.x + N_ATT;
    const bool is_att = cta < N_ATT;
    const int hkv = cta >> 3, rank = cta & 7;

    if (warp_id == 0) {
        const bool leader = elect_one();
        uint64_t pol;
        asm volatile("createpolicy.fractional.L2::evict_first.b64 %0, 1.0;" : "=l"(pol));
        const int nt = is_att ? NT_ATT : rank < N_FFN ? NT_FFN : 0;
        const int row0 = (rank * HKV + hkv) * SK - 128;
        auto coords = [&](int i, int& mi, int& c1, int& c2) {
            c2 = 0;
            if (is_att) {
                mi = (i >> 1) & 1; c1 = row0 + (i >> 2) * 128 + (i & 1) * 64;
                if (i >= NT_ATT - 12) { mi = ((i >> 3) & 1) ^ 1; c1 = row0 + 128 + SK - 256 + (i & 3) * 64; }
                if (i < 4) { mi = 2; c1 = 128 * i; c2 = cta; }
                if (i >= NT_ATT - 4) { mi = 3; c1 = 512 * hkv + 128 * (i - (NT_ATT - 4)); c2 = rank; }
            } else {
                mi = 5; c1 = FS * rank + 16 * (i - 16);
                if (i < 16) { mi = 4; c1 = 32 * i; c2 = 4 * rank; }
            }
        };
#pragma unroll
        for (int i = 0; i < D_START; i++)
            if (leader) mbar_init(bar_full + 8 * i, 1);
        if (nt > 0) {
#pragma unroll
            for (int i = 0; i < D_START; i++) {
                int mi, c1, c2;
                coords(i, mi, c1, c2);
                if (leader) {
                    mbar_expect_tx(bar_full + 8 * i, STAGE_BYTES);
                    tma3d(sb + SM_RING + i * STAGE_BYTES, &maps.m[mi], bar_full + 8 * i, c1, c2, pol);
                }
            }
        }
        const uint32_t t0 = timer_ns();
        __syncthreads();
        if (is_att) cluster_arrive();
        Cursor cur, lag, hi;
        cur.slot = D_START;
        lag.slot = D_START - D_MIN;
        const uint32_t step = is_att ? tau : tau * FFN_PACE / 16;
        uint32_t due = t0 + step * PACE_OFF / 16;
#pragma unroll 1
        for (int i = D_START; i < nt; i++) {
            int mi, c1, c2;
            coords(i, mi, c1, c2);
            const CUtensorMap* map = &maps.m[mi];
            const uint32_t dst = sb + SM_RING + cur.slot * STAGE_BYTES, bar = bar_full + 8 * cur.slot;
            const uint32_t lbar = is_att ? bar_full + 8 * lag.slot : bar_q, lph = is_att ? lag.phase : 0u;
            if (i >= STAGES) mbar_wait(bar + 8 * STAGES, cur.phase ^ 1u);
            if (leader) mbar_expect_tx(bar, STAGE_BYTES);
            int it = 0;
#pragma unroll 1
            while (!mbar_test(lbar, lph) && (int)(timer_ns() - due) < 0 && ++it < 4096) {
            }
            if (leader) tma3d(dst, map, bar, c1, c2, pol);
            if (i == I_GATE && leader) mbar_arrive(bar_gate);
            lag.adv(i == NT_ATT - 5 ? 1 + D_MIN - D_WO : 1);
            cur.adv(1);
            due += i >= I_FAST ? tau2 : step;
            if (i == NT_ATT - 5) due += step * WO_GAP / 16;
            if (i >= D_HI) {
                if (!mbar_test(bar_full + 8 * hi.slot, hi.phase)) due += step * SLIP / 16;
                hi.adv(1);
            }
        }
    } else if (warp_id == 1) {
        if (elect_one()) {
            if (sb & 1023u) __trap();
#pragma unroll
            for (int s = D_START; s < STAGES; s++) mbar_init(bar_full + 8 * s, 1);
#pragma unroll
            for (int s = 0; s < STAGES; s++) mbar_init(bar_empty + 8 * s, is_att ? 4 : 8);
            mbar_init(bar_ok, 1);
            mbar_init(bar_q, 1);
            mbar_init(bar_o, 1);
            mbar_init(bar_o + 8, 1);
            mbar_init(bar_gate, 1);
            asm volatile("fence.mbarrier_init.release.cluster;" ::: "memory");
            mbar_expect_tx(bar_q, 1024);
            mbar_expect_tx(bar_o, 7 * 512);
            mbar_expect_tx(bar_o + 8, 7 * 512);
        }
        __syncthreads();
        if (is_att) {
            cluster_arrive();
            mbar_wait(bar_gate, 0);
            if (lane == 0) {
                int it = 0;
                while (true) {
                    unsigned v;
                    asm volatile("ld.acquire.gpu.global.u32 %0, [%1];" : "=r"(v) : "l"(&g_ctr) : "memory");
                    if (v >= 8u) break;
                    __nanosleep(200);
                    if (++it > SPIN_LIMIT) __trap();
                }
            }
            __syncwarp();
            const int g = lane >> 2, t = lane & 3;
#pragma unroll 2
            for (int mt = 0; mt < 4; mt++) {
                const int col = rank * 64 + mt * 16 + g;
                float y[4] = {}, res[4];
#pragma unroll
                for (int i = 0; i < N_FFN; i++) {
                    const float4 v = __ldcg(g_gp + ((i * 8 + rank) * 4 + mt) * 32 + lane);
                    y[0] += v.x; y[1] += v.y; y[2] += v.z; y[3] += v.w;
                }
#pragma unroll
                for (int c = 0; c < 4; c++) {
                    const int cc = col + 8 * (c >> 1), bb = 2 * t + (c & 1);
                    const float z = rbf(rbf(y[c]) + __bfloat162float(b2[cc]));
                    y[c] = rbf(__fdividef(z, 1.0f + __expf(-z)));
                    res[c] = bb == hkv ? __bfloat162float(x[bb * DM + cc]) : 0.f;
                }
                *reinterpret_cast<float4*>(sp + SM_GATE + mt * 1024 + lane * 16) = make_float4(y[0], y[1], y[2], y[3]);
                *reinterpret_cast<float4*>(sp + SM_GATE + mt * 1024 + 512 + lane * 16) = make_float4(res[0], res[1], res[2], res[3]);
            }
            __syncwarp();
            if (lane == 0) {
                mbar_arrive(bar_ok);
                atomicInc(&g_ctr, N_CTA - 1);
            }
        } else if (rank == N_FFN) {
#pragma unroll 4
            for (int i = 0; i < 16; i++) reinterpret_cast<uint4*>(out)[i * 32 + lane] = make_uint4(0, 0, 0, 0);
            __syncwarp();
            if (lane == 0) {
                asm volatile("fence.acq_rel.gpu;" ::: "memory");
                atomicInc(&g_ctr, N_CTA - 1);
            }
        }
    } else {
        const int warp = warp_id - 2, tid = threadIdx.x - 64;
        const int g = lane >> 2, t = lane & 3;
        {
            uint4 xv[2];
#pragma unroll
            for (int i = 0; i < 2; i++) xv[i] = __ldg(reinterpret_cast<const uint4*>(x + warp * DM + i * 256 + lane * 8));
            __syncthreads();
            if (is_att) cluster_arrive();
            uint32_t w[8] = {xv[0].x, xv[0].y, xv[0].z, xv[0].w, xv[1].x, xv[1].y, xv[1].z, xv[1].w};
            float s0 = 0.f, s1 = 0.f;
#pragma unroll
            for (int i = 0; i < 8; i++) { s0 += bf_lo(w[i]); s1 += bf_hi(w[i]); }
            s0 += s1;
#pragma unroll
            for (int o = 16; o > 0; o >>= 1) s0 += __shfl_xor_sync(0xffffffffu, s0, o);
            const float mean = s0 * (1.0f / DM);
            s0 = 0.f; s1 = 0.f;
#pragma unroll
            for (int i = 0; i < 8; i++) {
                const float d0 = bf_lo(w[i]) - mean, d1 = bf_hi(w[i]) - mean;
                s0 += d0 * d0; s1 += d1 * d1;
            }
            s0 += s1;
#pragma unroll
            for (int o = 16; o > 0; o >>= 1) s0 += __shfl_xor_sync(0xffffffffu, s0, o);
            const uint32_t mb = pack_bf16(mean, mean);
            float sd;
            asm("sqrt.approx.f32 %0, %1;" : "=f"(sd) : "f"(rbf(rbf(s0 * (1.0f / DM)) + 1e-5f)));
            const float rs = rcp(rbf(sd));
#pragma unroll
            for (int i = 0; i < 8; i++) {
                const uint32_t d = sub_bf16x2(w[i], mb);
                w[i] = pack_bf16(bf_lo(d) * rs, bf_hi(d) * rs);
            }
#pragma unroll
            for (int i = 0; i < 2; i++)
                *reinterpret_cast<uint4*>(sp + SM_XN + (warp * XN_STRIDE + i * 256 + lane * 8) * 2) =
                    make_uint4(w[4 * i], w[4 * i + 1], w[4 * i + 2], w[4 * i + 3]);
        }
        bar_compute();
        const uint32_t* xn32 = reinterpret_cast<const uint32_t*>(sp + SM_XN) + g * (XN_STRIDE / 2) + t;
        const int krow = (lane & 7) + (lane >> 4) * 8;
        const int cbit = (lane >> 3) & 1;
        const int wq4 = warp & 3;
        Cursor cur;

        if (is_att) {
            cluster_wait();
            const uint32_t wbase = sb + SM_RING + krow * 128 + (((2 * wq4 + cbit) ^ (lane & 7)) << 4);
            const uint32_t abase = sb + SM_XN + (lane & 7) * (XN_STRIDE * 2) + (lane >> 3) * 16;
            if (warp < 4) {
                float acc[4][4] = {};
#pragma unroll 1
                for (int s = 0; s < 4; s++) {
                    uint32_t a[8][4], bf[4][4];
                    load_act(bf, abase + s * 256);
                    mbar_wait(bar_full + 8 * s, 0);
                    load_w(a, wbase + s * STAGE_BYTES);
                    mma_stage(acc, a, bf);
                    __syncwarp();
                    if (lane == 0) mbar_arrive(bar_empty + 8 * s);
                }
                const uint32_t q0 = movm_t(pack_bf16((acc[0][0] + acc[1][0]) + (acc[2][0] + acc[3][0]), (acc[0][1] + acc[1][1]) + (acc[2][1] + acc[3][1])));
                const uint32_t q1 = movm_t(pack_bf16((acc[0][2] + acc[1][2]) + (acc[2][2] + acc[3][2]), (acc[0][3] + acc[1][3]) + (acc[2][3] + acc[3][3])));
                st_async2(mapa(sb + SM_QIN + ((rank * 4 + warp) * 4 + t) * 8, g), q0, q1, mapa(bar_q, g));
            }
            uint2 qf[8];
            mbar_wait_cluster(bar_q, 0);
#pragma unroll
            for (int kk = 0; kk < 8; kk++) qf[kk] = *reinterpret_cast<const uint2*>(sp + SM_QIN + (((g & 3) * 8 + kk) * 4 + t) * 8);
            float o[8][4] = {};
            uint32_t mpk = 0xff7fff7fu;
            float m0 = bf_lo(mpk), m1 = bf_hi(mpk), l0 = 0.f, l1 = 0.f;
            uint32_t koff[4], voff[4];
#pragma unroll
            for (int i = 0; i < 4; i++) {
                koff[i] = (16 * wq4 + (lane & 7) + cbit * 8) * 128 + (((2 * i + (lane >> 4)) ^ (lane & 7)) << 4);
                voff[i] = (16 * wq4 + krow) * 128 + (((2 * i + cbit) ^ (lane & 7)) << 4);
            }
            uint32_t s01, s23, u01 = 0, u23 = 0;
            cur.adv(4 + (warp >> 2));
#pragma unroll 1
            for (int tile = 0;; tile++) {
                const bool last = tile >= KV_TILES / 2 - 2;
                if (tile == KV_TILES / 2 - 3) mbar_wait(bar_ok, 0);
                const uint32_t kbar = bar_full + 8 * cur.slot, vbar = kbar + 16;
                const uint32_t kb = sb + SM_RING + cur.slot * STAGE_BYTES, vb = kb + 2 * STAGE_BYTES;
                uint32_t a[8][4];
                mbar_wait(kbar, cur.phase);
#pragma unroll
                for (int i = 0; i < 8; i++) ldsm4(a[i], kb + (i >> 2) * 8192 + koff[i & 3]);
                const bool early = __all_sync(0xffffffffu, !last && mbar_test(vbar, cur.phase));
                float sa[4][4] = {};
#pragma unroll
                for (int i = 0; i < 8; i++) mma16816(sa[i & 3], a[i], qf[i].x, qf[i].y);
                __syncwarp();
                if (lane == 0) mbar_arrive(kbar + 8 * STAGES);
                if (early) {
#pragma unroll
                    for (int i = 0; i < 8; i++) ldsm4t(a[i], vb + (i >> 2) * 8192 + voff[i & 3]);
                }
                s01 = pack_bf16((sa[0][0] + sa[1][0]) + (sa[2][0] + sa[3][0]), (sa[0][1] + sa[1][1]) + (sa[2][1] + sa[3][1]));
                s23 = pack_bf16((sa[0][2] + sa[1][2]) + (sa[2][2] + sa[3][2]), (sa[0][3] + sa[1][3]) + (sa[2][3] + sa[3][3]));
                const float scale = 0.08838834764831845f;
                s01 = pack_bf16(bf_lo(s01) * scale, bf_hi(s01) * scale);
                s23 = pack_bf16(bf_lo(s23) * scale, bf_hi(s23) * scale);
                if (last) {
                    if (tile == KV_TILES / 2 - 1) break;
                    u01 = s01; u23 = s23;
                    cur.adv(2);
                    continue;
                }
                uint32_t mx = max_bf16x2(max_bf16x2(s01, s23), mpk);
                if (__any_sync(0xffffffffu, mx != mpk)) {
                    mx = max_bf16x2(mx, __shfl_xor_sync(0xffffffffu, mx, 4));
                    mx = max_bf16x2(mx, __shfl_xor_sync(0xffffffffu, mx, 8));
                    mx = max_bf16x2(mx, __shfl_xor_sync(0xffffffffu, mx, 16));
                    const float n0 = bf_lo(mx), n1 = bf_hi(mx);
                    const float a0 = ex2((m0 - n0) * LOG2E), a1 = ex2((m1 - n1) * LOG2E);
                    m0 = n0; m1 = n1; mpk = mx;
                    l0 *= a0; l1 *= a1;
#pragma unroll
                    for (int mt = 0; mt < 8; mt++) { o[mt][0] *= a0; o[mt][1] *= a1; o[mt][2] *= a0; o[mt][3] *= a1; }
                }
                const float p0 = ex2((bf_lo(s01) - m0) * LOG2E), p1 = ex2((bf_hi(s01) - m1) * LOG2E);
                const float p2 = ex2((bf_lo(s23) - m0) * LOG2E), p3 = ex2((bf_hi(s23) - m1) * LOG2E);
                l0 += p0 + p2; l1 += p1 + p3;
                const uint32_t pb0 = movm_t(pack_bf16(p0, p1)), pb1 = movm_t(pack_bf16(p2, p3));
                if (!early) {
                    mbar_wait(vbar, cur.phase);
#pragma unroll
                    for (int i = 0; i < 8; i++) ldsm4t(a[i], vb + (i >> 2) * 8192 + voff[i & 3]);
                }
#pragma unroll
                for (int i = 0; i < 8; i++) mma16816(o[i], a[i], pb0, pb1);
                __syncwarp();
                if (lane == 0) mbar_arrive(vbar + 8 * STAGES);
                cur.adv(4);
            }
            constexpr int SLOT_K = (NT_ATT - 12) % STAGES, SLOT_V = SLOT_K + 4;
            static_assert(SLOT_V + 4 <= STAGES, "last tiles must not wrap");
            constexpr uint32_t PH_LAST = ((NT_ATT - 12) / STAGES) & 1;
            const uint32_t orow = sb + SM_XN + rank * (XN_STRIDE * 2);
            const bool hi = t >= 2;
            {
                uint32_t mx = max_bf16x2(max_bf16x2(max_bf16x2(s01, s23), max_bf16x2(u01, u23)), mpk);
                mx = max_bf16x2(mx, __shfl_xor_sync(0xffffffffu, mx, 4));
                mx = max_bf16x2(mx, __shfl_xor_sync(0xffffffffu, mx, 8));
                mx = max_bf16x2(mx, __shfl_xor_sync(0xffffffffu, mx, 16));
                if (lane < 2) sts32(sb + SM_ML + lane * 32 + warp * 4, mx);
                bar_compute();
                const uint4 ma = lds128(sb + SM_ML + (t & 1) * 32), mb = lds128(sb + SM_ML + (t & 1) * 32 + 16);
                const uint32_t M = max_bf16x2(max_bf16x2(max_bf16x2(ma.x, ma.y), max_bf16x2(ma.z, ma.w)),
                                              max_bf16x2(max_bf16x2(mb.x, mb.y), max_bf16x2(mb.z, mb.w)));
                const float M0 = bf_lo(M), M1 = bf_hi(M);
                const float f0 = ex2((m0 - M0) * LOG2E), f1 = ex2((m1 - M1) * LOG2E);
                l0 *= f0; l1 *= f1;
#pragma unroll
                for (int j = 0; j < 2; j++) {
                    const uint32_t a01 = j ? s01 : u01, a23 = j ? s23 : u23;
                    const float p0 = ex2((bf_lo(a01) - M0) * LOG2E), p1 = ex2((bf_hi(a01) - M1) * LOG2E);
                    const float p2 = ex2((bf_lo(a23) - M0) * LOG2E), p3 = ex2((bf_hi(a23) - M1) * LOG2E);
                    l0 += p0 + p2; l1 += p1 + p3;
                    const uint32_t pb0 = movm_t(pack_bf16(p0, p1)), pb1 = movm_t(pack_bf16(p2, p3));
                    if (lane < 16) *reinterpret_cast<uint2*>(sp + SM_H + lane * 144 + (warp >> 2) * 64 + j * 32 + wq4 * 8) = make_uint2(pb0, pb1);
                }
                uint8_t* part = sp + SM_RING + (SLOT_K + (warp >> 2)) * STAGE_BYTES + wq4 * 2048 + (t >> 1) * 1024 +
                                ((2 * g + (t & 1)) ^ (4 * ((t >> 1) ^ (warp >> 2)))) * 16;
#pragma unroll
                for (int i = 0; i < 4; i++)
                    *reinterpret_cast<float4*>(part + i * 256) =
                        make_float4((hi ? o[4 + i][0] : o[i][0]) * f0, (hi ? o[4 + i][1] : o[i][1]) * f1,
                                    (hi ? o[4 + i][2] : o[i][2]) * f0, (hi ? o[4 + i][3] : o[i][3]) * f1);
#pragma unroll
                for (int of = 4; of < 32; of <<= 1) {
                    l0 += __shfl_xor_sync(0xffffffffu, l0, of);
                    l1 += __shfl_xor_sync(0xffffffffu, l1, of);
                }
                if (lane < 2) *reinterpret_cast<float2*>(sp + SM_ML + 64 + lane * 64 + warp * 8) = make_float2(l0, l1);
            }
            bar_compute();
            {
                uint4 pf[4];
#pragma unroll
                for (int i = 0; i < 4; i++) pf[i] = *reinterpret_cast<const uint4*>(sp + SM_H + (lane & 15) * 144 + (lane >> 4) * 64 + i * 16);
                const uint8_t* psum = sp + SM_RING + (SLOT_K + (t >> 1)) * STAGE_BYTES + warp * 256 +
                                      ((2 * g + (t & 1)) ^ (4 * ((t >> 1) ^ (warp >> 2)))) * 16;
                float acc[4][4];
#pragma unroll
                for (int w = 0; w < 4; w++) {
                    const float4 v = *reinterpret_cast<const float4*>(psum + w * 2048);
                    acc[w][0] = v.x; acc[w][1] = v.y; acc[w][2] = v.z; acc[w][3] = v.w;
                }
                float L0 = 0.f, L1 = 0.f;
#pragma unroll
                for (int i = 0; i < 4; i++) {
                    const float4 v = *reinterpret_cast<const float4*>(sp + SM_ML + 64 + (t & 1) * 64 + i * 16);
                    L0 += v.x + v.z; L1 += v.y + v.w;
                }
                const float i0 = rcp(L0), i1 = rcp(L1);
                const uint32_t vbase = wbase + SLOT_V * STAGE_BYTES + (warp >> 2) * 8192;
                const uint32_t ost = orow + (g & 3) * 256 + warp * 32 + (g >> 2) * 16 + t * 4;
#pragma unroll
                for (int j = 0; j < 4; j++) {
                    uint32_t a[4][4];
                    const bool on = (lane >> 4) == (j & 1);
                    const uint4 pa = pf[j & 2], pb = pf[(j & 2) + 1];
                    mbar_wait(bar_full + 8 * (SLOT_V + j), PH_LAST);
#pragma unroll
                    for (int ks = 0; ks < 4; ks++) ldsm4t(a[ks], vbase + j * STAGE_BYTES + ks * 2048);
                    mma16816(acc[0], a[0], on ? pa.x : 0u, on ? pa.y : 0u);
                    mma16816(acc[1], a[1], on ? pa.z : 0u, on ? pa.w : 0u);
                    mma16816(acc[2], a[2], on ? pb.x : 0u, on ? pb.y : 0u);
                    mma16816(acc[3], a[3], on ? pb.z : 0u, on ? pb.w : 0u);
                }
#pragma unroll
                for (int c = 0; c < 4; c++) { acc[0][c] += acc[2][c]; acc[1][c] += acc[3][c]; }
                const float c0 = acc[0][0] + acc[1][0], c1 = acc[0][1] + acc[1][1], c2 = acc[0][2] + acc[1][2], c3 = acc[0][3] + acc[1][3];
                const float r0 = (hi ? c2 : c0) + __shfl_xor_sync(0xffffffffu, hi ? c0 : c2, 2);
                const float r1 = (hi ? c3 : c1) + __shfl_xor_sync(0xffffffffu, hi ? c1 : c3, 2);
                sts32(ost, movm_t(pack_bf16(r0 * i0, r1 * i1)));
            }
            bar_compute();
            if (warp != rank) {
                const uint4 u0 = lds128(orow + lane * 16), u1 = lds128(orow + lane * 16 + 512);
                const uint32_t odst = mapa(orow + lane * 16, warp), obar = mapa(bar_o, warp);
                st_async4(odst, u0, obar);
                st_async4(odst + 512, u1, obar + 8);
            }
            if (warp < 4) {
                __nv_bfloat16* dst = out + g * DM + rank * 64 + warp * 16 + 2 * t;
                constexpr uint32_t ph = ((NT_ATT - 4) / STAGES) & 1;
                static_assert((NT_ATT - 4) % STAGES == 0, "wo must start in slot 0");
                uint32_t a[4][8][4], bf[4][4][4];
                float acc[4][4] = {};
                const bool w01 = __all_sync(0xffffffffu, mbar_test(bar_full, ph) & mbar_test(bar_full + 8, ph));
                const bool o01 = __all_sync(0xffffffffu, mbar_test_cluster(bar_o) & mbar_test_cluster(bar_o + 8));
                if (!w01) mbar_wait(bar_full, ph);
                load_w(a[0], wbase);
                if (!w01) mbar_wait(bar_full + 8, ph);
                load_w(a[1], wbase + STAGE_BYTES);
                if (!o01) mbar_wait_cluster(bar_o, 0);
                asm volatile("fence.acquire.sync_restrict::shared::cluster.cluster;" ::: "memory");
                load_act(bf[0], abase);
                load_act(bf[1], abase + 256);
                if (!o01) mbar_wait_cluster(bar_o + 8, 0);
                const bool w2 = __all_sync(0xffffffffu, mbar_test(bar_full + 16, ph)), w3 = __all_sync(0xffffffffu, mbar_test(bar_full + 24, ph));
                load_act(bf[2], abase + 512);
                load_act(bf[3], abase + 768);
                mma_stage(acc, a[0], bf[0]);
                if (w2) load_w(a[2], wbase + 2 * STAGE_BYTES);
                mma_stage(acc, a[1], bf[1]);
                if (!w2) { mbar_wait(bar_full + 16, ph); load_w(a[2], wbase + 2 * STAGE_BYTES); }
                if (w3) load_w(a[3], wbase + 3 * STAGE_BYTES);
                mma_stage(acc, a[2], bf[2]);
                if (!w3) { mbar_wait(bar_full + 24, ph); load_w(a[3], wbase + 3 * STAGE_BYTES); }
                mma_stage(acc, a[3], bf[3]);
                float r[4];
                const uint4 gt = lds128(sb + SM_GATE + warp * 1024 + lane * 16), rs = lds128(sb + SM_GATE + warp * 1024 + 512 + lane * 16);
#pragma unroll
                for (int c = 0; c < 4; c++) r[c] = (acc[0][c] + acc[1][c]) + (acc[2][c] + acc[3][c]);
                red_bf16x2(dst, movm_t(pack_bf16(fmaf(r[0], __uint_as_float(gt.x), __uint_as_float(rs.x)),
                                                 fmaf(r[1], __uint_as_float(gt.y), __uint_as_float(rs.y)))));
                red_bf16x2(dst + 8, movm_t(pack_bf16(fmaf(r[2], __uint_as_float(gt.z), __uint_as_float(rs.z)),
                                                     fmaf(r[3], __uint_as_float(gt.w), __uint_as_float(rs.w)))));
            }
        } else if (rank < N_FFN) {
            if (tid < FS / 8) *reinterpret_cast<uint4*>(sp + SM_QIN + tid * 16) = __ldg(reinterpret_cast<const uint4*>(b1 + FS * rank) + tid);
            float acc[4][4] = {};
#pragma unroll 1
            for (int kt = 0; kt < 16; kt++) {
                mbar_wait(bar_full + 8 * cur.slot, cur.phase);
                const uint32_t base = sb + SM_RING + cur.slot * STAGE_BYTES + (warp >> 1) * 4096 + krow * 128;
#pragma unroll
                for (int ks = 0; ks < 2; ks++) {
                    const uint32_t b0 = xn32[kt * 16 + ks * 8], b1r = xn32[kt * 16 + ks * 8 + 4];
#pragma unroll
                    for (int mt = 0; mt < 2; mt++) {
                        uint32_t a[4];
                        ldsm4t(a, base + ks * 2048 + (((4 * (warp & 1) + 2 * mt + cbit) ^ (lane & 7)) << 4));
                        mma16816(acc[mt], a, b0, b1r);
                    }
                }
                __syncwarp();
                if (lane == 0) mbar_arrive(bar_empty + 8 * cur.slot);
                cur.adv(1);
            }
            bar_compute();
            __nv_bfloat16* hs = reinterpret_cast<__nv_bfloat16*>(sp + SM_H);
            const __nv_bfloat16* b1s = reinterpret_cast<const __nv_bfloat16*>(sp + SM_QIN);
#pragma unroll
            for (int mt = 0; mt < 2; mt++)
#pragma unroll
                for (int c = 0; c < 4; c++) {
                    const int u = warp * 32 + mt * 16 + g + (c >> 1) * 8;
                    const float hv = rbf(rbf(acc[mt][c]) + __bfloat162float(b1s[u]));
                    const float inner = 0.7978845608028654f * (hv + 0.044715f * hv * hv * hv);
                    hs[(2 * t + (c & 1)) * H_STRIDE + u] = __float2bfloat16_rn(0.5f * hv * (1.0f + tanhf(inner)));
                    acc[mt][c] = 0.f;
                }
            bar_compute();
            const uint32_t* h32 = reinterpret_cast<const uint32_t*>(sp + SM_H) + g * (H_STRIDE / 2) + t;
#pragma unroll 1
            for (int kt = 0; kt < 16; kt++) {
                const uint32_t b0 = h32[kt * 8], b1r = h32[kt * 8 + 4];
                mbar_wait(bar_full + 8 * cur.slot, cur.phase);
                const uint32_t base = sb + SM_RING + cur.slot * STAGE_BYTES + warp * 2048 + krow * 128;
#pragma unroll
                for (int mt = 0; mt < 4; mt++) {
                    uint32_t a[4];
                    ldsm4t(a, base + (((2 * mt + cbit) ^ (lane & 7)) << 4));
                    mma16816(acc[mt], a, b0, b1r);
                }
                __syncwarp();
                if (lane == 0) mbar_arrive(bar_empty + 8 * cur.slot);
                cur.adv(1);
            }
#pragma unroll
            for (int mt = 0; mt < 4; mt++)
                g_gp[((rank * 8 + warp) * 4 + mt) * 32 + lane] = make_float4(acc[mt][0], acc[mt][1], acc[mt][2], acc[mt][3]);
            bar_compute();
            if (tid == 0) {
                asm volatile("fence.acq_rel.gpu;" ::: "memory");
                atomicInc(&g_ctr, N_CTA - 1);
            }
        }
    }
}

typedef CUresult (*EncodeTiledFn)(CUtensorMap*, CUtensorMapDataType, cuuint32_t, void*, const cuuint64_t*, const cuuint64_t*,
                                  const cuuint32_t*, const cuuint32_t*, CUtensorMapInterleave, CUtensorMapSwizzle,
                                  CUtensorMapL2promotion, CUtensorMapFloatOOBfill);

void encode(EncodeTiledFn fn, CUtensorMap* m, const void* ptr, int rows, int cols, int nrow, int nblk, CUtensorMapL2promotion promo) {
    const cuuint64_t dims[3] = {64, (cuuint64_t)rows, (cuuint64_t)cols / 64}, strides[2] = {(cuuint64_t)cols * 2, 128};
    const cuuint32_t box[3] = {64, (cuuint32_t)nrow, (cuuint32_t)nblk}, es[3] = {1, 1, 1};
    fn(m, CU_TENSOR_MAP_DATA_TYPE_BFLOAT16, 3, const_cast<void*>(ptr), dims, strides, box, es,
       CU_TENSOR_MAP_INTERLEAVE_NONE, CU_TENSOR_MAP_SWIZZLE_128B, promo, CU_TENSOR_MAP_FLOAT_OOB_FILL_NONE);
}

}

extern "C" void kernel_launch(void* const* d_in, const int* in_sizes, int n_in, void* d_out, int out_size) {
    (void)in_sizes; (void)n_in; (void)out_size;
    EncodeTiledFn fn = nullptr;
    cudaDriverEntryPointQueryResult qr;
    cudaGetDriverEntryPoint("cuTensorMapEncodeTiled", (void**)&fn, cudaEnableDefault, &qr);
    cudaFuncSetAttribute(fused_decode_kernel, cudaFuncAttributeMaxDynamicSharedMemorySize, SMEM_BYTES);

    int dev = 0, khz = 0, bits = 0;
    cudaGetDevice(&dev);
    cudaDeviceGetAttribute(&khz, cudaDevAttrMemoryClockRate, dev);
    cudaDeviceGetAttribute(&bits, cudaDevAttrGlobalMemoryBusWidth, dev);
    const double rel = (khz > 0 && bits > 0) ? (2619000.0 * 5120.0) / ((double)khz * bits) : 1.0;
    const uint32_t tau = (uint32_t)(TAU_NS * rel + 0.5), tau2 = (uint32_t)(TAU2_NS * rel + 0.5);

    int nclusters = 0;
    {
        cudaLaunchConfig_t cfg = {};
        cfg.gridDim = dim3(N_CTA); cfg.blockDim = dim3(THREADS); cfg.dynamicSmemBytes = SMEM_BYTES;
        cudaLaunchAttribute at;
        at.id = cudaLaunchAttributeClusterDimension;
        at.val.clusterDim.x = 8; at.val.clusterDim.y = 1; at.val.clusterDim.z = 1;
        cfg.attrs = &at; cfg.numAttrs = 1;
        if (cudaOccupancyMaxActiveClusters(&nclusters, fused_decode_kernel, &cfg) != cudaSuccess) { nclusters = 0; cudaGetLastError(); }
    }
    const int shift = nclusters >= N_CTA / 8 ? 0 : 8;

    Maps maps;
    encode(fn, &maps.m[0], d_in[1], NB * HKV * SK, DH, 64, 2, CU_TENSOR_MAP_L2_PROMOTION_L2_256B);
    encode(fn, &maps.m[1], d_in[2], NB * HKV * SK, DH, 64, 2, CU_TENSOR_MAP_L2_PROMOTION_L2_256B);
    encode(fn, &maps.m[2], d_in[3], DM, HQ * DH, 128, 1, CU_TENSOR_MAP_L2_PROMOTION_L2_128B);
    encode(fn, &maps.m[3], d_in[4], HQ * DH, DM, 128, 1, CU_TENSOR_MAP_L2_PROMOTION_L2_128B);
    encode(fn, &maps.m[4], d_in[6], DM, FF, 32, 4, CU_TENSOR_MAP_L2_PROMOTION_L2_256B);
    encode(fn, &maps.m[5], d_in[8], FF, DM, 16, 8, CU_TENSOR_MAP_L2_PROMOTION_L2_256B);
    fused_decode_kernel<<<N_CTA, THREADS, SMEM_BYTES>>>(maps, (const __nv_bfloat16*)d_in[0], (const __nv_bfloat16*)d_in[7],
                                                        (const __nv_bfloat16*)d_in[9], (__nv_bfloat16*)d_out, d_in[3], tau, tau2, shift);
}
```

```cpp
#include <cuda_runtime.h>
#include <cuda_bf16.h>
#include <cuda.h>
#include <stdint.h>

namespace {

constexpr int NB = 8, DM = 512, HQ = 32, HKV = 8, SK = 4096, DH = 128, FF = 1792;
constexpr int N_ATT = 64, N_FFN = 7, N_CTA = 72;
constexpr int THREADS = 320;
constexpr int STAGES = 12;
constexpr int TAU_NS = 329, TAU2_NS = 320;
constexpr int I_FAST = 92;
constexpr int D_START = 4;
constexpr int PACE_OFF = 36;
constexpr int D_MIN = 4, D_WO = 3;
constexpr int D_HI = 6, SLIP = 1;
constexpr int WO_GAP = 16;
constexpr int FFN_PACE = 48;
constexpr int I_GATE = 104;
constexpr int PREF_BYTES = 16384;
constexpr int STAGE_BYTES = 16384;
constexpr int KV_TILES = 64;
constexpr int NT_ATT = 4 + 2 * KV_TILES + 4;
constexpr int FS = 256;
constexpr int NT_FFN = 32;
constexpr int XN_STRIDE = DM + 8;
constexpr int H_STRIDE = FS + 8;

constexpr int SM_RING = 0;
constexpr int SM_XN = SM_RING + STAGES * STAGE_BYTES;
constexpr int SM_QIN = SM_XN + NB * XN_STRIDE * 2;
constexpr int SM_ML = SM_QIN + 1024;
constexpr int SM_H = SM_ML + 256;
constexpr int SM_GATE = SM_H + NB * H_STRIDE * 2;
constexpr int SM_BAR = SM_GATE + 4096;
constexpr int SM_END = SM_BAR + (2 * STAGES + 6) * 8;
constexpr int SMEM_BYTES = SM_END + 128;
static_assert(SMEM_BYTES <= 232448, "smem");
static_assert(SM_QIN % 16 == 0 && SM_BAR % 8 == 0, "align");

__device__ float4 g_gp[N_FFN * 8 * 4 * 32];
__device__ unsigned g_ctr;


constexpr int SPIN_LIMIT = 1 << 22;

struct Maps { CUtensorMap m[6]; };

__device__ __forceinline__ void mbar_init(uint32_t bar, uint32_t cnt) {
    asm volatile("mbarrier.init.shared::cta.b64 [%0], %1;" ::"r"(bar), "r"(cnt) : "memory");
}
__device__ __forceinline__ void mbar_expect_tx(uint32_t bar, uint32_t bytes) {
    asm volatile("mbarrier.arrive.expect_tx.shared::cta.b64 _, [%0], %1;" ::"r"(bar), "r"(bytes) : "memory");
}
__device__ __forceinline__ void mbar_arrive(uint32_t bar) {
    asm volatile("mbarrier.arrive.shared::cta.b64 _, [%0];" ::"r"(bar) : "memory");
}
__device__ __forceinline__ void mbar_wait(uint32_t bar, uint32_t parity) {
    uint32_t ok;
    int it = 0;
    do {
        asm volatile("{\n.reg .pred p;\nmbarrier.try_wait.parity.shared::cta.b64 p, [%1], %2;\nselp.u32 %0, 1, 0, p;\n}"
                     : "=r"(ok) : "r"(bar), "r"(parity) : "memory");
        if (++it > SPIN_LIMIT) __trap();
    } while (!ok);
}
__device__ __forceinline__ void mbar_wait_cluster(uint32_t bar, uint32_t parity) {
    uint32_t ok;
    int it = 0;
    do {
        asm volatile("{\n.reg .pred p;\nmbarrier.try_wait.parity.relaxed.cluster.shared::cta.b64 p, [%1], %2;\nselp.u32 %0, 1, 0, p;\n}"
                     : "=r"(ok) : "r"(bar), "r"(parity) : "memory");
        if (++it > SPIN_LIMIT) __trap();
    } while (!ok);
    asm volatile("fence.acquire.sync_restrict::shared::cluster.cluster;" ::: "memory");
}
__device__ __forceinline__ bool mbar_test(uint32_t bar, uint32_t parity) {
    uint32_t ok;
    asm volatile("{\n.reg .pred p;\nmbarrier.test_wait.parity.shared::cta.b64 p, [%1], %2;\nselp.u32 %0, 1, 0, p;\n}"
                 : "=r"(ok) : "r"(bar), "r"(parity) : "memory");
    return ok;
}
__device__ __forceinline__ void tma3d(uint32_t dst, const CUtensorMap* m, uint32_t bar, int c1, int c2, uint64_t pol) {
    asm volatile("cp.async.bulk.tensor.3d.shared::cluster.global.mbarrier::complete_tx::bytes.L2::cache_hint [%0], [%1, {%3, %4, %5}], [%2], %6;"
                 ::"r"(dst), "l"(m), "r"(bar), "r"(0), "r"(c1), "r"(c2), "l"(pol) : "memory");
}
__device__ __forceinline__ uint32_t mapa(uint32_t addr, uint32_t rank) {
    uint32_t r;
    asm("mapa.shared::cluster.u32 %0, %1, %2;" : "=r"(r) : "r"(addr), "r"(rank));
    return r;
}
__device__ __forceinline__ void st_async2(uint32_t addr, uint32_t a, uint32_t b, uint32_t bar) {
    asm volatile("st.async.shared::cluster.mbarrier::complete_tx::bytes.v2.b32 [%0], {%1, %2}, [%3];"
                 ::"r"(addr), "r"(a), "r"(b), "r"(bar) : "memory");
}
__device__ __forceinline__ void st_async4(uint32_t addr, const uint4& v, uint32_t bar) {
    asm volatile("st.async.shared::cluster.mbarrier::complete_tx::bytes.v4.b32 [%0], {%1, %2, %3, %4}, [%5];"
                 ::"r"(addr), "r"(v.x), "r"(v.y), "r"(v.z), "r"(v.w), "r"(bar) : "memory");
}
__device__ __forceinline__ void cluster_arrive() { asm volatile("barrier.cluster.arrive.relaxed.aligned;" ::: "memory"); }
__device__ __forceinline__ void cluster_wait() { asm volatile("barrier.cluster.wait.aligned;" ::: "memory"); }
__device__ __forceinline__ void sts32(uint32_t addr, uint32_t v) {
    asm volatile("st.shared.b32 [%0], %1;" ::"r"(addr), "r"(v) : "memory");
}
__device__ __forceinline__ uint4 lds128(uint32_t addr) {
    uint4 v;
    asm volatile("ld.shared.v4.b32 {%0, %1, %2, %3}, [%4];" : "=r"(v.x), "=r"(v.y), "=r"(v.z), "=r"(v.w) : "r"(addr) : "memory");
    return v;
}
__device__ __forceinline__ void ldsm4(uint32_t (&r)[4], uint32_t addr) {
    asm volatile("ldmatrix.sync.aligned.m8n8.x4.shared.b16 {%0, %1, %2, %3}, [%4];"
                 : "=r"(r[0]), "=r"(r[1]), "=r"(r[2]), "=r"(r[3]) : "r"(addr) : "memory");
}
__device__ __forceinline__ void ldsm4t(uint32_t (&r)[4], uint32_t addr) {
    asm volatile("ldmatrix.sync.aligned.m8n8.x4.trans.shared.b16 {%0, %1, %2, %3}, [%4];"
                 : "=r"(r[0]), "=r"(r[1]), "=r"(r[2]), "=r"(r[3]) : "r"(addr) : "memory");
}
__device__ __forceinline__ void mma16816(float (&c)[4], const uint32_t (&a)[4], uint32_t b0, uint32_t b1) {
    asm volatile("mma.sync.aligned.m16n8k16.row.col.f32.bf16.bf16.f32 {%0, %1, %2, %3}, {%4, %5, %6, %7}, {%8, %9}, {%0, %1, %2, %3};"
                 : "+f"(c[0]), "+f"(c[1]), "+f"(c[2]), "+f"(c[3])
                 : "r"(a[0]), "r"(a[1]), "r"(a[2]), "r"(a[3]), "r"(b0), "r"(b1));
}
__device__ __forceinline__ uint32_t movm_t(uint32_t a) {
    uint32_t d;
    asm volatile("movmatrix.sync.aligned.m8n8.trans.b16 %0, %1;" : "=r"(d) : "r"(a));
    return d;
}
__device__ __forceinline__ uint32_t pack_bf16(float lo, float hi) {
    uint32_t d;
    asm("cvt.rn.bf16x2.f32 %0, %1, %2;" : "=r"(d) : "f"(hi), "f"(lo));
    return d;
}
__device__ __forceinline__ float bf_lo(uint32_t v) { return __uint_as_float(v << 16); }
__device__ __forceinline__ float bf_hi(uint32_t v) { return __uint_as_float(v & 0xffff0000u); }
__device__ __forceinline__ float rbf(float x) { return __uint_as_float(pack_bf16(0.f, x)); }
__device__ __forceinline__ uint32_t max_bf16x2(uint32_t a, uint32_t b) {
    uint32_t d;
    asm("max.bf16x2 %0, %1, %2;" : "=r"(d) : "r"(a), "r"(b));
    return d;
}
__device__ __forceinline__ uint32_t sub_bf16x2(uint32_t a, uint32_t b) {
    uint32_t d;
    asm("sub.rn.bf16x2 %0, %1, %2;" : "=r"(d) : "r"(a), "r"(b));
    return d;
}
__device__ __forceinline__ float ex2(float x) {
    float y;
    asm("ex2.approx.ftz.f32 %0, %1;" : "=f"(y) : "f"(x));
    return y;
}
__device__ __forceinline__ float rcp(float x) {
    float y;
    asm("rcp.approx.ftz.f32 %0, %1;" : "=f"(y) : "f"(x));
    return y;
}
__device__ __forceinline__ void red_bf16x2(__nv_bfloat16* p, uint32_t v) {
    asm volatile("red.relaxed.gpu.global.add.noftz.bf16x2 [%0], %1;" ::"l"(p), "r"(v) : "memory");
}
__device__ __forceinline__ bool elect_one() {
    uint32_t p;
    asm volatile("{\n.reg .pred P;\nelect.sync _|P, 0xffffffff;\nselp.u32 %0, 1, 0, P;\n}" : "=r"(p));
    return p;
}
__device__ __forceinline__ uint32_t timer_ns() {
    uint32_t t;
    asm volatile("mov.u32 %0, %%globaltimer_lo;" : "=r"(t));
    return t;
}
__device__ __forceinline__ void bar_all() { asm volatile("barrier.sync 2, 320;" ::: "memory"); }
__device__ __forceinline__ void bar_compute() { asm volatile("barrier.sync 1, 256;" ::: "memory"); }

struct Cursor {
    int slot = 0;
    uint32_t phase = 0;
    __device__ __forceinline__ void adv(int n) { slot += n; if (slot >= STAGES) { slot -= STAGES; phase ^= 1u; } }
};

constexpr float LOG2E = 1.4426950408889634f;

__device__ __forceinline__ void load_w(uint32_t (&a)[8][4], uint32_t addr) {
#pragma unroll
    for (int ks = 0; ks < 8; ks++) ldsm4t(a[ks], addr + ks * 2048);
}
__device__ __forceinline__ void load_act(uint32_t (&b)[4][4], uint32_t addr) {
#pragma unroll
    for (int i = 0; i < 4; i++) ldsm4(b[i], addr + i * 64);
}
__device__ __forceinline__ void mma_stage(float (&acc)[4][4], const uint32_t (&a)[8][4], const uint32_t (&b)[4][4]) {
#pragma unroll
    for (int ks = 0; ks < 8; ks++) mma16816(acc[ks & 3], a[ks], b[ks >> 1][2 * (ks & 1)], b[ks >> 1][2 * (ks & 1) + 1]);
}
__device__ __forceinline__ bool mbar_test_cluster(uint32_t bar) {
    uint32_t ok;
    asm volatile("{\n.reg .pred p;\nmbarrier.test_wait.parity.relaxed.cluster.shared::cta.b64 p, [%1], 0;\nselp.u32 %0, 1, 0, p;\n}"
                 : "=r"(ok) : "r"(bar) : "memory");
    return ok;
}

__global__ void __cluster_dims__(8, 1, 1) __launch_bounds__(THREADS, 1)
fused_decode_kernel(const __grid_constant__ Maps maps, const __nv_bfloat16* __restrict__ x, const __nv_bfloat16* __restrict__ b1,
                    const __nv_bfloat16* __restrict__ b2, __nv_bfloat16* __restrict__ out, const void* wq, const uint32_t tau, const uint32_t tau2,
                    const int shift) {
    extern __shared__ __align__(1024) uint8_t smem_raw[];
    uint32_t sb;
    asm volatile("{\n.reg .u64 a;\ncvta.to.shared.u64 a, %1;\ncvt.u32.u64 %0, a;\n}" : "=r"(sb) : "l"(smem_raw));
    uint8_t* sp = smem_raw;
    const uint32_t bar_full = sb + SM_BAR, bar_empty = bar_full + 8 * STAGES;
    const uint32_t bar_ok = bar_empty + 8 * STAGES, bar_q = bar_ok + 8, bar_o = bar_q + 8, bar_gate = bar_o + 16;

    if (threadIdx.x == 0 && blockIdx.x < N_ATT)
        asm volatile("cp.async.bulk.prefetch.L2.global [%0], %1;"
                     ::"l"(reinterpret_cast<const char*>(wq) + (size_t)blockIdx.x * PREF_BYTES), "r"(PREF_BYTES) : "memory");
    const int warp_id = __shfl_sync(0xffffffffu, (int)(threadIdx.x >> 5), 0), lane = threadIdx.x & 31;
    const int cta = (int)blockIdx.x >= shift ? blockIdx.x - shift : blockIdx.x + N_ATT;
    const bool is_att = cta < N_ATT;
    const int hkv = cta >> 3, rank = cta & 7;

    if (warp_id == 0) {
        const bool leader = elect_one();
        uint64_t pol;
        asm volatile("createpolicy.fractional.L2::evict_first.b64 %0, 1.0;" : "=l"(pol));
        const int nt = is_att ? NT_ATT : rank < N_FFN ? NT_FFN : 0;
        const int row0 = (rank * HKV + hkv) * SK - 128;
        auto coords = [&](int i, int& mi, int& c1, int& c2) {
            c2 = 0;
            if (is_att) {
                mi = (i >> 1) & 1; c1 = row0 + (i >> 2) * 128 + (i & 1) * 64;
                if (i >= NT_ATT - 12) { mi = ((i >> 3) & 1) ^ 1; c1 = row0 + 128 + SK - 256 + (i & 3) * 64; }
                if (i < 4) { mi = 2; c1 = 128 * i; c2 = cta; }
                if (i >= NT_ATT - 4) { mi = 3; c1 = 512 * hkv + 128 * (i - (NT_ATT - 4)); c2 = rank; }
            } else {
                mi = 5; c1 = FS * rank + 16 * (i - 16);
                if (i < 16) { mi = 4; c1 = 32 * i; c2 = 4 * rank; }
            }
        };
#pragma unroll
        for (int i = 0; i < D_START; i++)
            if (leader) mbar_init(bar_full + 8 * i, 1);
        if (nt > 0) {
#pragma unroll
            for (int i = 0; i < D_START; i++) {
                int mi, c1, c2;
                coords(i, mi, c1, c2);
                if (leader) {
                    mbar_expect_tx(bar_full + 8 * i, STAGE_BYTES);
                    tma3d(sb + SM_RING + i * STAGE_BYTES, &maps.m[mi], bar_full + 8 * i, c1, c2, pol);
                }
            }
        }
        const uint32_t t0 = timer_ns();
        __syncwarp();
        bar_all();
        if (is_att) cluster_arrive();
        Cursor cur, lag, hi;
        cur.slot = D_START;
        lag.slot = D_START - D_MIN;
        const uint32_t step = is_att ? tau : tau * FFN_PACE / 16;
        uint32_t due = t0 + step * PACE_OFF / 16;
#pragma unroll 1
        for (int i = D_START; i < nt; i++) {
            int mi, c1, c2;
            coords(i, mi, c1, c2);
            const CUtensorMap* map = &maps.m[mi];
            const uint32_t dst = sb + SM_RING + cur.slot * STAGE_BYTES, bar = bar_full + 8 * cur.slot;
            const uint32_t lbar = is_att ? bar_full + 8 * lag.slot : bar_q, lph = is_att ? lag.phase : 0u;
            if (i >= STAGES) mbar_wait(bar + 8 * STAGES, cur.phase ^ 1u);
            if (leader) mbar_expect_tx(bar, STAGE_BYTES);
            int it = 0;
#pragma unroll 1
            while (!mbar_test(lbar, lph) && (int)(timer_ns() - due) < 0 && ++it < 4096) {
            }
            if (leader) tma3d(dst, map, bar, c1, c2, pol);
            if (i == I_GATE && leader) mbar_arrive(bar_gate);
            lag.adv(i == NT_ATT - 5 ? 1 + D_MIN - D_WO : 1);
            cur.adv(1);
            due += i >= I_FAST ? tau2 : step;
            if (i == NT_ATT - 5) due += step * WO_GAP / 16;
            if (i >= D_HI) {
                if (!mbar_test(bar_full + 8 * hi.slot, hi.phase)) due += step * SLIP / 16;
                hi.adv(1);
            }
        }
    } else if (warp_id == 1) {
        if (elect_one()) {
            if (sb & 1023u) __trap();
#pragma unroll
            for (int s = D_START; s < STAGES; s++) mbar_init(bar_full + 8 * s, 1);
#pragma unroll
            for (int s = 0; s < STAGES; s++) mbar_init(bar_empty + 8 * s, is_att ? 4 : 8);
            mbar_init(bar_ok, 1);
            mbar_init(bar_q, 1);
            mbar_init(bar_o, 1);
            mbar_init(bar_o + 8, 1);
            mbar_init(bar_gate, 1);
            asm volatile("fence.mbarrier_init.release.cluster;" ::: "memory");
            mbar_expect_tx(bar_q, 1024);
            mbar_expect_tx(bar_o, 7 * 512);
            mbar_expect_tx(bar_o + 8, 7 * 512);
        }
        __syncwarp();
        bar_all();
        if (is_att) {
            cluster_arrive();
            mbar_wait(bar_gate, 0);
            if (lane == 0) {
                int it = 0;
                while (true) {
                    unsigned v;
                    asm volatile("ld.acquire.gpu.global.u32 %0, [%1];" : "=r"(v) : "l"(&g_ctr) : "memory");
                    if (v >= 8u) break;
                    __nanosleep(200);
                    if (++it > SPIN_LIMIT) __trap();
                }
            }
            __syncwarp();
            const int g = lane >> 2, t = lane & 3;
#pragma unroll 2
            for (int mt = 0; mt < 4; mt++) {
                const int col = rank * 64 + mt * 16 + g;
                float y[4] = {}, res[4];
#pragma unroll
                for (int i = 0; i < N_FFN; i++) {
                    const float4 v = __ldcg(g_gp + ((i * 8 + rank) * 4 + mt) * 32 + lane);
                    y[0] += v.x; y[1] += v.y; y[2] += v.z; y[3] += v.w;
                }
#pragma unroll
                for (int c = 0; c < 4; c++) {
                    const int cc = col + 8 * (c >> 1), bb = 2 * t + (c & 1);
                    const float z = rbf(rbf(y[c]) + __bfloat162float(b2[cc]));
                    y[c] = rbf(__fdividef(z, 1.0f + __expf(-z)));
                    res[c] = bb == hkv ? __bfloat162float(x[bb * DM + cc]) : 0.f;
                }
                *reinterpret_cast<float4*>(sp + SM_GATE + mt * 1024 + lane * 16) = make_float4(y[0], y[1], y[2], y[3]);
                *reinterpret_cast<float4*>(sp + SM_GATE + mt * 1024 + 512 + lane * 16) = make_float4(res[0], res[1], res[2], res[3]);
            }
            __syncwarp();
            if (lane == 0) {
                mbar_arrive(bar_ok);
                atomicInc(&g_ctr, N_CTA - 1);
            }
        } else if (rank == N_FFN) {
#pragma unroll 4
            for (int i = 0; i < 16; i++) reinterpret_cast<uint4*>(out)[i * 32 + lane] = make_uint4(0, 0, 0, 0);
            __syncwarp();
            if (lane == 0) {
                asm volatile("fence.acq_rel.gpu;" ::: "memory");
                atomicInc(&g_ctr, N_CTA - 1);
            }
        }
    } else {
        const int warp = warp_id - 2, tid = threadIdx.x - 64;
        const int g = lane >> 2, t = lane & 3;
        {
            uint4 xv[2];
#pragma unroll
            for (int i = 0; i < 2; i++) xv[i] = __ldg(reinterpret_cast<const uint4*>(x + warp * DM + i * 256 + lane * 8));
            bar_all();
            if (is_att) cluster_arrive();
            uint32_t w[8] = {xv[0].x, xv[0].y, xv[0].z, xv[0].w, xv[1].x, xv[1].y, xv[1].z, xv[1].w};
            float s0 = 0.f, s1 = 0.f;
#pragma unroll
            for (int i = 0; i < 8; i++) { s0 += bf_lo(w[i]); s1 += bf_hi(w[i]); }
            s0 += s1;
#pragma unroll
            for (int o = 16; o > 0; o >>= 1) s0 += __shfl_xor_sync(0xffffffffu, s0, o);
            const float mean = s0 * (1.0f / DM);
            s0 = 0.f; s1 = 0.f;
#pragma unroll
            for (int i = 0; i < 8; i++) {
                const float d0 = bf_lo(w[i]) - mean, d1 = bf_hi(w[i]) - mean;
                s0 += d0 * d0; s1 += d1 * d1;
            }
            s0 += s1;
#pragma unroll
            for (int o = 16; o > 0; o >>= 1) s0 += __shfl_xor_sync(0xffffffffu, s0, o);
            const uint32_t mb = pack_bf16(mean, mean);
            float sd;
            asm("sqrt.approx.f32 %0, %1;" : "=f"(sd) : "f"(rbf(rbf(s0 * (1.0f / DM)) + 1e-5f)));
            const float rs = rcp(rbf(sd));
#pragma unroll
            for (int i = 0; i < 8; i++) {
                const uint32_t d = sub_bf16x2(w[i], mb);
                w[i] = pack_bf16(bf_lo(d) * rs, bf_hi(d) * rs);
            }
#pragma unroll
            for (int i = 0; i < 2; i++)
                *reinterpret_cast<uint4*>(sp + SM_XN + (warp * XN_STRIDE + i * 256 + lane * 8) * 2) =
                    make_uint4(w[4 * i], w[4 * i + 1], w[4 * i + 2], w[4 * i + 3]);
        }
        bar_compute();
        const uint32_t* xn32 = reinterpret_cast<const uint32_t*>(sp + SM_XN) + g * (XN_STRIDE / 2) + t;
        const int krow = (lane & 7) + (lane >> 4) * 8;
        const int cbit = (lane >> 3) & 1;
        const int wq4 = warp & 3;
        Cursor cur;

        if (is_att) {
            cluster_wait();
            const uint32_t wbase = sb + SM_RING + krow * 128 + (((2 * wq4 + cbit) ^ (lane & 7)) << 4);
            const uint32_t abase = sb + SM_XN + (lane & 7) * (XN_STRIDE * 2) + (lane >> 3) * 16;
            if (warp < 4) {
                float acc[4][4] = {};
#pragma unroll 1
                for (int s = 0; s < 4; s++) {
                    uint32_t a[8][4], bf[4][4];
                    load_act(bf, abase + s * 256);
                    mbar_wait(bar_full + 8 * s, 0);
                    load_w(a, wbase + s * STAGE_BYTES);
                    mma_stage(acc, a, bf);
                    __syncwarp();
                    if (lane == 0) mbar_arrive(bar_empty + 8 * s);
                }
                const uint32_t q0 = movm_t(pack_bf16((acc[0][0] + acc[1][0]) + (acc[2][0] + acc[3][0]), (acc[0][1] + acc[1][1]) + (acc[2][1] + acc[3][1])));
                const uint32_t q1 = movm_t(pack_bf16((acc[0][2] + acc[1][2]) + (acc[2][2] + acc[3][2]), (acc[0][3] + acc[1][3]) + (acc[2][3] + acc[3][3])));
                st_async2(mapa(sb + SM_QIN + ((rank * 4 + warp) * 4 + t) * 8, g), q0, q1, mapa(bar_q, g));
            }
            uint2 qf[8];
            mbar_wait_cluster(bar_q, 0);
#pragma unroll
            for (int kk = 0; kk < 8; kk++) qf[kk] = *reinterpret_cast<const uint2*>(sp + SM_QIN + (((g & 3) * 8 + kk) * 4 + t) * 8);
            float o[8][4] = {};
            uint32_t mpk = 0xff7fff7fu;
            float m0 = bf_lo(mpk), m1 = bf_hi(mpk), l0 = 0.f, l1 = 0.f;
            uint32_t koff[4], voff[4];
#pragma unroll
            for (int i = 0; i < 4; i++) {
                koff[i] = (16 * wq4 + (lane & 7) + cbit * 8) * 128 + (((2 * i + (lane >> 4)) ^ (lane & 7)) << 4);
                voff[i] = (16 * wq4 + krow) * 128 + (((2 * i + cbit) ^ (lane & 7)) << 4);
            }
            uint32_t s01, s23, u01 = 0, u23 = 0;
            cur.adv(4 + (warp >> 2));
#pragma unroll 1
            for (int tile = 0;; tile++) {
                const bool last = tile >= KV_TILES / 2 - 2;
                if (tile == KV_TILES / 2 - 3) mbar_wait(bar_ok, 0);
                const uint32_t kbar = bar_full + 8 * cur.slot, vbar = kbar + 16;
                const uint32_t kb = sb + SM_RING + cur.slot * STAGE_BYTES, vb = kb + 2 * STAGE_BYTES;
                uint32_t a[8][4];
                mbar_wait(kbar, cur.phase);
#pragma unroll
                for (int i = 0; i < 8; i++) ldsm4(a[i], kb + (i >> 2) * 8192 + koff[i & 3]);
                const bool early = __all_sync(0xffffffffu, !last && mbar_test(vbar, cur.phase));
                float sa[4][4] = {};
#pragma unroll
                for (int i = 0; i < 8; i++) mma16816(sa[i & 3], a[i], qf[i].x, qf[i].y);
                __syncwarp();
                if (lane == 0) mbar_arrive(kbar + 8 * STAGES);
                if (early) {
#pragma unroll
                    for (int i = 0; i < 8; i++) ldsm4t(a[i], vb + (i >> 2) * 8192 + voff[i & 3]);
                }
                s01 = pack_bf16((sa[0][0] + sa[1][0]) + (sa[2][0] + sa[3][0]), (sa[0][1] + sa[1][1]) + (sa[2][1] + sa[3][1]));
                s23 = pack_bf16((sa[0][2] + sa[1][2]) + (sa[2][2] + sa[3][2]), (sa[0][3] + sa[1][3]) + (sa[2][3] + sa[3][3]));
                const float scale = 0.08838834764831845f;
                s01 = pack_bf16(bf_lo(s01) * scale, bf_hi(s01) * scale);
                s23 = pack_bf16(bf_lo(s23) * scale, bf_hi(s23) * scale);
                if (last) {
                    if (tile == KV_TILES / 2 - 1) break;
                    u01 = s01; u23 = s23;
                    cur.adv(2);
                    continue;
                }
                uint32_t mx = max_bf16x2(max_bf16x2(s01, s23), mpk);
                if (__any_sync(0xffffffffu, mx != mpk)) {
                    mx = max_bf16x2(mx, __shfl_xor_sync(0xffffffffu, mx, 4));
                    mx = max_bf16x2(mx, __shfl_xor_sync(0xffffffffu, mx, 8));
                    mx = max_bf16x2(mx, __shfl_xor_sync(0xffffffffu, mx, 16));
                    const float n0 = bf_lo(mx), n1 = bf_hi(mx);
                    const float a0 = ex2((m0 - n0) * LOG2E), a1 = ex2((m1 - n1) * LOG2E);
                    m0 = n0; m1 = n1; mpk = mx;
                    l0 *= a0; l1 *= a1;
#pragma unroll
                    for (int mt = 0; mt < 8; mt++) { o[mt][0] *= a0; o[mt][1] *= a1; o[mt][2] *= a0; o[mt][3] *= a1; }
                }
                const float p0 = ex2((bf_lo(s01) - m0) * LOG2E), p1 = ex2((bf_hi(s01) - m1) * LOG2E);
                const float p2 = ex2((bf_lo(s23) - m0) * LOG2E), p3 = ex2((bf_hi(s23) - m1) * LOG2E);
                l0 += p0 + p2; l1 += p1 + p3;
                const uint32_t pb0 = movm_t(pack_bf16(p0, p1)), pb1 = movm_t(pack_bf16(p2, p3));
                if (!early) {
                    mbar_wait(vbar, cur.phase);
#pragma unroll
                    for (int i = 0; i < 8; i++) ldsm4t(a[i], vb + (i >> 2) * 8192 + voff[i & 3]);
                }
#pragma unroll
                for (int i = 0; i < 8; i++) mma16816(o[i], a[i], pb0, pb1);
                __syncwarp();
                if (lane == 0) mbar_arrive(vbar + 8 * STAGES);
                cur.adv(4);
            }
            constexpr int SLOT_K = (NT_ATT - 12) % STAGES, SLOT_V = SLOT_K + 4;
            static_assert(SLOT_V + 4 <= STAGES, "last tiles must not wrap");
            constexpr uint32_t PH_LAST = ((NT_ATT - 12) / STAGES) & 1;
            const uint32_t orow = sb + SM_XN + rank * (XN_STRIDE * 2);
            const bool hi = t >= 2;
            {
                uint32_t mx = max_bf16x2(max_bf16x2(max_bf16x2(s01, s23), max_bf16x2(u01, u23)), mpk);
                mx = max_bf16x2(mx, __shfl_xor_sync(0xffffffffu, mx, 4));
                mx = max_bf16x2(mx, __shfl_xor_sync(0xffffffffu, mx, 8));
                mx = max_bf16x2(mx, __shfl_xor_sync(0xffffffffu, mx, 16));
                if (lane < 2) sts32(sb + SM_ML + lane * 32 + warp * 4, mx);
                bar_compute();
                const uint4 ma = lds128(sb + SM_ML + (t & 1) * 32), mb = lds128(sb + SM_ML + (t & 1) * 32 + 16);
                const uint32_t M = max_bf16x2(max_bf16x2(max_bf16x2(ma.x, ma.y), max_bf16x2(ma.z, ma.w)),
                                              max_bf16x2(max_bf16x2(mb.x, mb.y), max_bf16x2(mb.z, mb.w)));
                const float M0 = bf_lo(M), M1 = bf_hi(M);
                const float f0 = ex2((m0 - M0) * LOG2E), f1 = ex2((m1 - M1) * LOG2E);
                l0 *= f0; l1 *= f1;
#pragma unroll
                for (int j = 0; j < 2; j++) {
                    const uint32_t a01 = j ? s01 : u01, a23 = j ? s23 : u23;
                    const float p0 = ex2((bf_lo(a01) - M0) * LOG2E), p1 = ex2((bf_hi(a01) - M1) * LOG2E);
                    const float p2 = ex2((bf_lo(a23) - M0) * LOG2E), p3 = ex2((bf_hi(a23) - M1) * LOG2E);
                    l0 += p0 + p2; l1 += p1 + p3;
                    const uint32_t pb0 = movm_t(pack_bf16(p0, p1)), pb1 = movm_t(pack_bf16(p2, p3));
                    if (lane < 16) *reinterpret_cast<uint2*>(sp + SM_H + lane * 144 + (warp >> 2) * 64 + j * 32 + wq4 * 8) = make_uint2(pb0, pb1);
                }
                uint8_t* part = sp + SM_RING + (SLOT_K + (warp >> 2)) * STAGE_BYTES + wq4 * 2048 + (t >> 1) * 1024 +
                                ((2 * g + (t & 1)) ^ (4 * ((t >> 1) ^ (warp >> 2)))) * 16;
#pragma unroll
                for (int i = 0; i < 4; i++)
                    *reinterpret_cast<float4*>(part + i * 256) =
                        make_float4((hi ? o[4 + i][0] : o[i][0]) * f0, (hi ? o[4 + i][1] : o[i][1]) * f1,
                                    (hi ? o[4 + i][2] : o[i][2]) * f0, (hi ? o[4 + i][3] : o[i][3]) * f1);
#pragma unroll
                for (int of = 4; of < 32; of <<= 1) {
                    l0 += __shfl_xor_sync(0xffffffffu, l0, of);
                    l1 += __shfl_xor_sync(0xffffffffu, l1, of);
                }
                if (lane < 2) *reinterpret_cast<float2*>(sp + SM_ML + 64 + lane * 64 + warp * 8) = make_float2(l0, l1);
            }
            bar_compute();
            {
                uint4 pf[4];
#pragma unroll
                for (int i = 0; i < 4; i++) pf[i] = *reinterpret_cast<const uint4*>(sp + SM_H + (lane & 15) * 144 + (lane >> 4) * 64 + i * 16);
                const uint8_t* psum = sp + SM_RING + (SLOT_K + (t >> 1)) * STAGE_BYTES + warp * 256 +
                                      ((2 * g + (t & 1)) ^ (4 * ((t >> 1) ^ (warp >> 2)))) * 16;
                float acc[4][4];
#pragma unroll
                for (int w = 0; w < 4; w++) {
                    const float4 v = *reinterpret_cast<const float4*>(psum + w * 2048);
                    acc[w][0] = v.x; acc[w][1] = v.y; acc[w][2] = v.z; acc[w][3] = v.w;
                }
                float L0 = 0.f, L1 = 0.f;
#pragma unroll
                for (int i = 0; i < 4; i++) {
                    const float4 v = *reinterpret_cast<const float4*>(sp + SM_ML + 64 + (t & 1) * 64 + i * 16);
                    L0 += v.x + v.z; L1 += v.y + v.w;
                }
                const float i0 = rcp(L0), i1 = rcp(L1);
                const uint32_t vbase = wbase + SLOT_V * STAGE_BYTES + (warp >> 2) * 8192;
                const uint32_t ost = orow + (g & 3) * 256 + warp * 32 + (g >> 2) * 16 + t * 4;
#pragma unroll
                for (int j = 0; j < 4; j++) {
                    uint32_t a[4][4];
                    const bool on = (lane >> 4) == (j & 1);
                    const uint4 pa = pf[j & 2], pb = pf[(j & 2) + 1];
                    mbar_wait(bar_full + 8 * (SLOT_V + j), PH_LAST);
#pragma unroll
                    for (int ks = 0; ks < 4; ks++) ldsm4t(a[ks], vbase + j * STAGE_BYTES + ks * 2048);
                    mma16816(acc[0], a[0], on ? pa.x : 0u, on ? pa.y : 0u);
                    mma16816(acc[1], a[1], on ? pa.z : 0u, on ? pa.w : 0u);
                    mma16816(acc[2], a[2], on ? pb.x : 0u, on ? pb.y : 0u);
                    mma16816(acc[3], a[3], on ? pb.z : 0u, on ? pb.w : 0u);
                }
#pragma unroll
                for (int c = 0; c < 4; c++) { acc[0][c] += acc[2][c]; acc[1][c] += acc[3][c]; }
                const float c0 = acc[0][0] + acc[1][0], c1 = acc[0][1] + acc[1][1], c2 = acc[0][2] + acc[1][2], c3 = acc[0][3] + acc[1][3];
                const float r0 = (hi ? c2 : c0) + __shfl_xor_sync(0xffffffffu, hi ? c0 : c2, 2);
                const float r1 = (hi ? c3 : c1) + __shfl_xor_sync(0xffffffffu, hi ? c1 : c3, 2);
                sts32(ost, movm_t(pack_bf16(r0 * i0, r1 * i1)));
            }
            bar_compute();
            if (warp != rank) {
                const uint4 u0 = lds128(orow + lane * 16), u1 = lds128(orow + lane * 16 + 512);
                const uint32_t odst = mapa(orow + lane * 16, warp), obar = mapa(bar_o, warp);
                st_async4(odst, u0, obar);
                st_async4(odst + 512, u1, obar + 8);
            }
            if (warp < 4) {
                __nv_bfloat16* dst = out + __shfl_sync(0xffffffffu, g * DM + rank * 64 + warp * 16 + 2 * t, lane);
                constexpr uint32_t ph = ((NT_ATT - 4) / STAGES) & 1;
                static_assert((NT_ATT - 4) % STAGES == 0, "wo must start in slot 0");
                uint32_t a[4][8][4], bf[4][4][4];
                float acc[4][4] = {};
                mbar_wait(bar_full, ph);
                load_w(a[0], wbase);
                bool w1;
                int it = 0;
#pragma unroll 1
                while (!(w1 = __all_sync(0xffffffffu, mbar_test(bar_full + 8, ph))) && !__all_sync(0xffffffffu, mbar_test_cluster(bar_o)))
                    if (++it > SPIN_LIMIT) __trap();
                if (w1) load_w(a[1], wbase + STAGE_BYTES);
                mbar_wait_cluster(bar_o, 0);
                load_act(bf[0], abase);
                load_act(bf[1], abase + 256);
                mbar_wait_cluster(bar_o + 8, 0);
                load_act(bf[2], abase + 512);
                load_act(bf[3], abase + 768);
                if (!w1) mbar_wait(bar_full + 8, ph);
                const bool w2 = __all_sync(0xffffffffu, mbar_test(bar_full + 16, ph)), w3 = __all_sync(0xffffffffu, mbar_test(bar_full + 24, ph));
                if (!w1) load_w(a[1], wbase + STAGE_BYTES);
                mma_stage(acc, a[0], bf[0]);
                if (w2) load_w(a[2], wbase + 2 * STAGE_BYTES);
                mma_stage(acc, a[1], bf[1]);
                if (!w2) { mbar_wait(bar_full + 16, ph); load_w(a[2], wbase + 2 * STAGE_BYTES); }
                if (w3) load_w(a[3], wbase + 3 * STAGE_BYTES);
                mma_stage(acc, a[2], bf[2]);
                if (!w3) { mbar_wait(bar_full + 24, ph); load_w(a[3], wbase + 3 * STAGE_BYTES); }
                mma_stage(acc, a[3], bf[3]);
                float r[4];
                const uint4 gt = lds128(sb + SM_GATE + warp * 1024 + lane * 16), rs = lds128(sb + SM_GATE + warp * 1024 + 512 + lane * 16);
#pragma unroll
                for (int c = 0; c < 4; c++) r[c] = (acc[0][c] + acc[1][c]) + (acc[2][c] + acc[3][c]);
                red_bf16x2(dst, movm_t(pack_bf16(fmaf(r[0], __uint_as_float(gt.x), __uint_as_float(rs.x)),
                                                 fmaf(r[1], __uint_as_float(gt.y), __uint_as_float(rs.y)))));
                red_bf16x2(dst + 8, movm_t(pack_bf16(fmaf(r[2], __uint_as_float(gt.z), __uint_as_float(rs.z)),
                                                     fmaf(r[3], __uint_as_float(gt.w), __uint_as_float(rs.w)))));
            }
        } else if (rank < N_FFN) {
            if (tid < FS / 8) *reinterpret_cast<uint4*>(sp + SM_QIN + tid * 16) = __ldg(reinterpret_cast<const uint4*>(b1 + FS * rank) + tid);
            float acc[4][4] = {};
#pragma unroll 1
            for (int kt = 0; kt < 16; kt++) {
                mbar_wait(bar_full + 8 * cur.slot, cur.phase);
                const uint32_t base = sb + SM_RING + cur.slot * STAGE_BYTES + (warp >> 1) * 4096 + krow * 128;
#pragma unroll
                for (int ks = 0; ks < 2; ks++) {
                    const uint32_t b0 = xn32[kt * 16 + ks * 8], b1r = xn32[kt * 16 + ks * 8 + 4];
#pragma unroll
                    for (int mt = 0; mt < 2; mt++) {
                        uint32_t a[4];
                        ldsm4t(a, base + ks * 2048 + (((4 * (warp & 1) + 2 * mt + cbit) ^ (lane & 7)) << 4));
                        mma16816(acc[mt], a, b0, b1r);
                    }
                }
                __syncwarp();
                if (lane == 0) mbar_arrive(bar_empty + 8 * cur.slot);
                cur.adv(1);
            }
            bar_compute();
            __nv_bfloat16* hs = reinterpret_cast<__nv_bfloat16*>(sp + SM_H);
            const __nv_bfloat16* b1s = reinterpret_cast<const __nv_bfloat16*>(sp + SM_QIN);
#pragma unroll
            for (int mt = 0; mt < 2; mt++)
#pragma unroll
                for (int c = 0; c < 4; c++) {
                    const int u = warp * 32 + mt * 16 + g + (c >> 1) * 8;
                    const float hv = rbf(rbf(acc[mt][c]) + __bfloat162float(b1s[u]));
                    const float inner = 0.7978845608028654f * (hv + 0.044715f * hv * hv * hv);
                    hs[(2 * t + (c & 1)) * H_STRIDE + u] = __float2bfloat16_rn(0.5f * hv * (1.0f + tanhf(inner)));
                    acc[mt][c] = 0.f;
                }
            bar_compute();
            const uint32_t* h32 = reinterpret_cast<const uint32_t*>(sp + SM_H) + g * (H_STRIDE / 2) + t;
#pragma unroll 1
            for (int kt = 0; kt < 16; kt++) {
                const uint32_t b0 = h32[kt * 8], b1r = h32[kt * 8 + 4];
                mbar_wait(bar_full + 8 * cur.slot, cur.phase);
                const uint32_t base = sb + SM_RING + cur.slot * STAGE_BYTES + warp * 2048 + krow * 128;
#pragma unroll
                for (int mt = 0; mt < 4; mt++) {
                    uint32_t a[4];
                    ldsm4t(a, base + (((2 * mt + cbit) ^ (lane & 7)) << 4));
                    mma16816(acc[mt], a, b0, b1r);
                }
                __syncwarp();
                if (lane == 0) mbar_arrive(bar_empty + 8 * cur.slot);
                cur.adv(1);
            }
#pragma unroll
            for (int mt = 0; mt < 4; mt++)
                g_gp[((rank * 8 + warp) * 4 + mt) * 32 + lane] = make_float4(acc[mt][0], acc[mt][1], acc[mt][2], acc[mt][3]);
            bar_compute();
            if (tid == 0) {
                asm volatile("fence.acq_rel.gpu;" ::: "memory");
                atomicInc(&g_ctr, N_CTA - 1);
            }
        }
    }
}

typedef CUresult (*EncodeTiledFn)(CUtensorMap*, CUtensorMapDataType, cuuint32_t, void*, const cuuint64_t*, const cuuint64_t*,
                                  const cuuint32_t*, const cuuint32_t*, CUtensorMapInterleave, CUtensorMapSwizzle,
                                  CUtensorMapL2promotion, CUtensorMapFloatOOBfill);

void encode(EncodeTiledFn fn, CUtensorMap* m, const void* ptr, int rows, int cols, int nrow, int nblk, CUtensorMapL2promotion promo) {
    const cuuint64_t dims[3] = {64, (cuuint64_t)rows, (cuuint64_t)cols / 64}, strides[2] = {(cuuint64_t)cols * 2, 128};
    const cuuint32_t box[3] = {64, (cuuint32_t)nrow, (cuuint32_t)nblk}, es[3] = {1, 1, 1};
    fn(m, CU_TENSOR_MAP_DATA_TYPE_BFLOAT16, 3, const_cast<void*>(ptr), dims, strides, box, es,
       CU_TENSOR_MAP_INTERLEAVE_NONE, CU_TENSOR_MAP_SWIZZLE_128B, promo, CU_TENSOR_MAP_FLOAT_OOB_FILL_NONE);
}

}

extern "C" void kernel_launch(void* const* d_in, const int* in_sizes, int n_in, void* d_out, int out_size) {
    (void)in_sizes; (void)n_in; (void)out_size;
    EncodeTiledFn fn = nullptr;
    cudaDriverEntryPointQueryResult qr;
    cudaGetDriverEntryPoint("cuTensorMapEncodeTiled", (void**)&fn, cudaEnableDefault, &qr);
    cudaFuncSetAttribute(fused_decode_kernel, cudaFuncAttributeMaxDynamicSharedMemorySize, SMEM_BYTES);

    int dev = 0, khz = 0, bits = 0;
    cudaGetDevice(&dev);
    cudaDeviceGetAttribute(&khz, cudaDevAttrMemoryClockRate, dev);
    cudaDeviceGetAttribute(&bits, cudaDevAttrGlobalMemoryBusWidth, dev);
    const double rel = (khz > 0 && bits > 0) ? (2619000.0 * 5120.0) / ((double)khz * bits) : 1.0;
    const uint32_t tau = (uint32_t)(TAU_NS * rel + 0.5), tau2 = (uint32_t)(TAU2_NS * rel + 0.5);

    int nclusters = 0;
    {
        cudaLaunchConfig_t cfg = {};
        cfg.gridDim = dim3(N_CTA); cfg.blockDim = dim3(THREADS); cfg.dynamicSmemBytes = SMEM_BYTES;
        cudaLaunchAttribute at;
        at.id = cudaLaunchAttributeClusterDimension;
        at.val.clusterDim.x = 8; at.val.clusterDim.y = 1; at.val.clusterDim.z = 1;
        cfg.attrs = &at; cfg.numAttrs = 1;
        if (cudaOccupancyMaxActiveClusters(&nclusters, fused_decode_kernel, &cfg) != cudaSuccess) { nclusters = 0; cudaGetLastError(); }
    }
    const int shift = nclusters >= N_CTA / 8 ? 0 : 8;

    Maps maps;
    encode(fn, &maps.m[0], d_in[1], NB * HKV * SK, DH, 64, 2, CU_TENSOR_MAP_L2_PROMOTION_L2_256B);
    encode(fn, &maps.m[1], d_in[2], NB * HKV * SK, DH, 64, 2, CU_TENSOR_MAP_L2_PROMOTION_L2_256B);
    encode(fn, &maps.m[2], d_in[3], DM, HQ * DH, 128, 1, CU_TENSOR_MAP_L2_PROMOTION_L2_128B);
    encode(fn, &maps.m[3], d_in[4], HQ * DH, DM, 128, 1, CU_TENSOR_MAP_L2_PROMOTION_L2_128B);
    encode(fn, &maps.m[4], d_in[6], DM, FF, 32, 4, CU_TENSOR_MAP_L2_PROMOTION_L2_256B);
    encode(fn, &maps.m[5], d_in[8], FF, DM, 16, 8, CU_TENSOR_MAP_L2_PROMOTION_L2_256B);
    fused_decode_kernel<<<N_CTA, THREADS, SMEM_BYTES>>>(maps, (const __nv_bfloat16*)d_in[0], (const __nv_bfloat16*)d_in[7],
                                                        (const __nv_bfloat16*)d_in[9], (__nv_bfloat16*)d_out, d_in[3], tau, tau2, shift);
}
```

```cpp
#include <cuda_runtime.h>
#include <cuda_bf16.h>
#include <cuda.h>
#include <stdint.h>

namespace {

constexpr int NB = 8, DM = 512, HQ = 32, HKV = 8, SK = 4096, DH = 128, FF = 1792;
constexpr int N_ATT = 64, N_FFN = 7, N_CTA = 72;
constexpr int THREADS = 320;
constexpr int STAGES = 12;
constexpr int TAU_NS = 329, TAU2_NS = 320;
constexpr int I_FAST = 92;
constexpr int D_START = 4;
constexpr int PACE_OFF = 36;
constexpr int D_MIN = 4, D_WO = 3;
constexpr int D_HI = 6, SLIP = 1;
constexpr int WO_GAP = 16;
constexpr int FFN_PACE = 48;
constexpr int I_GATE = 104;
constexpr int PREF_BYTES = 16384;
constexpr int STAGE_BYTES = 16384;
constexpr int KV_TILES = 64;
constexpr int NT_ATT = 4 + 2 * KV_TILES + 4;
constexpr int FS = 256;
constexpr int NT_FFN = 32;
constexpr int XN_STRIDE = DM + 8;
constexpr int H_STRIDE = FS + 8;

constexpr int SM_RING = 0;
constexpr int SM_XN = SM_RING + STAGES * STAGE_BYTES;
constexpr int SM_QIN = SM_XN + NB * XN_STRIDE * 2;
constexpr int SM_ML = SM_QIN + 1024;
constexpr int SM_H = SM_ML + 256;
constexpr int SM_GATE = SM_H + NB * H_STRIDE * 2;
constexpr int SM_BAR = SM_GATE + 4096;
constexpr int SMEM_BYTES = SM_BAR + (2 * STAGES + 6) * 8;
static_assert(SMEM_BYTES <= 232448, "smem");
static_assert(SM_QIN % 16 == 0 && SM_BAR % 8 == 0, "align");

__device__ float4 g_gp[N_FFN * 8 * 4 * 32];
__device__ unsigned g_ctr;

constexpr int SPIN_LIMIT = 1 << 22;

struct Maps { CUtensorMap m[6]; };

__device__ __forceinline__ void mbar_init(uint32_t bar, uint32_t cnt) {
    asm volatile("mbarrier.init.shared::cta.b64 [%0], %1;" ::"r"(bar), "r"(cnt) : "memory");
}
__device__ __forceinline__ void mbar_expect_tx(uint32_t bar, uint32_t bytes) {
    asm volatile("mbarrier.arrive.expect_tx.shared::cta.b64 _, [%0], %1;" ::"r"(bar), "r"(bytes) : "memory");
}
__device__ __forceinline__ void mbar_arrive(uint32_t bar) {
    asm volatile("mbarrier.arrive.shared::cta.b64 _, [%0];" ::"r"(bar) : "memory");
}
__device__ __forceinline__ void mbar_wait(uint32_t bar, uint32_t parity) {
    uint32_t ok;
    int it = 0;
    do {
        asm volatile("{\n.reg .pred p;\nmbarrier.try_wait.parity.shared::cta.b64 p, [%1], %2;\nselp.u32 %0, 1, 0, p;\n}"
                     : "=r"(ok) : "r"(bar), "r"(parity) : "memory");
        if (++it > SPIN_LIMIT) __trap();
    } while (!ok);
}
__device__ __forceinline__ void mbar_wait_cluster(uint32_t bar, uint32_t parity) {
    uint32_t ok;
    int it = 0;
    do {
        asm volatile("{\n.reg .pred p;\nmbarrier.try_wait.parity.relaxed.cluster.shared::cta.b64 p, [%1], %2;\nselp.u32 %0, 1, 0, p;\n}"
                     : "=r"(ok) : "r"(bar), "r"(parity) : "memory");
        if (++it > SPIN_LIMIT) __trap();
    } while (!ok);
    asm volatile("fence.acquire.sync_restrict::shared::cluster.cluster;" ::: "memory");
}
__device__ __forceinline__ bool mbar_test(uint32_t bar, uint32_t parity) {
    uint32_t ok;
    asm volatile("{\n.reg .pred p;\nmbarrier.test_wait.parity.shared::cta.b64 p, [%1], %2;\nselp.u32 %0, 1, 0, p;\n}"
                 : "=r"(ok) : "r"(bar), "r"(parity) : "memory");
    return ok;
}
__device__ __forceinline__ void tma3d(uint32_t dst, const CUtensorMap* m, uint32_t bar, int c1, int c2, uint64_t pol) {
    asm volatile("cp.async.bulk.tensor.3d.shared::cluster.global.mbarrier::complete_tx::bytes.L2::cache_hint [%0], [%1, {%3, %4, %5}], [%2], %6;"
                 ::"r"(dst), "l"(m), "r"(bar), "r"(0), "r"(c1), "r"(c2), "l"(pol) : "memory");
}
__device__ __forceinline__ uint32_t mapa(uint32_t addr, uint32_t rank) {
    uint32_t r;
    asm("mapa.shared::cluster.u32 %0, %1, %2;" : "=r"(r) : "r"(addr), "r"(rank));
    return r;
}
__device__ __forceinline__ void st_async2(uint32_t addr, uint32_t a, uint32_t b, uint32_t bar) {
    asm volatile("st.async.shared::cluster.mbarrier::complete_tx::bytes.v2.b32 [%0], {%1, %2}, [%3];"
                 ::"r"(addr), "r"(a), "r"(b), "r"(bar) : "memory");
}
__device__ __forceinline__ void st_async4(uint32_t addr, const uint4& v, uint32_t bar) {
    asm volatile("st.async.shared::cluster.mbarrier::complete_tx::bytes.v4.b32 [%0], {%1, %2, %3, %4}, [%5];"
                 ::"r"(addr), "r"(v.x), "r"(v.y), "r"(v.z), "r"(v.w), "r"(bar) : "memory");
}
__device__ __forceinline__ void cluster_arrive() { asm volatile("barrier.cluster.arrive.relaxed.aligned;" ::: "memory"); }
__device__ __forceinline__ void cluster_wait() { asm volatile("barrier.cluster.wait.aligned;" ::: "memory"); }
__device__ __forceinline__ void sts32(uint32_t addr, uint32_t v) {
    asm volatile("st.shared.b32 [%0], %1;" ::"r"(addr), "r"(v) : "memory");
}
__device__ __forceinline__ uint4 lds128(uint32_t addr) {
    uint4 v;
    asm volatile("ld.shared.v4.b32 {%0, %1, %2, %3}, [%4];" : "=r"(v.x), "=r"(v.y), "=r"(v.z), "=r"(v.w) : "r"(addr) : "memory");
    return v;
}
__device__ __forceinline__ void ldsm4(uint32_t (&r)[4], uint32_t addr) {
    asm volatile("ldmatrix.sync.aligned.m8n8.x4.shared.b16 {%0, %1, %2, %3}, [%4];"
                 : "=r"(r[0]), "=r"(r[1]), "=r"(r[2]), "=r"(r[3]) : "r"(addr) : "memory");
}
__device__ __forceinline__ void ldsm4t(uint32_t (&r)[4], uint32_t addr) {
    asm volatile("ldmatrix.sync.aligned.m8n8.x4.trans.shared.b16 {%0, %1, %2, %3}, [%4];"
                 : "=r"(r[0]), "=r"(r[1]), "=r"(r[2]), "=r"(r[3]) : "r"(addr) : "memory");
}
__device__ __forceinline__ void mma16816(float (&c)[4], const uint32_t (&a)[4], uint32_t b0, uint32_t b1) {
    asm volatile("mma.sync.aligned.m16n8k16.row.col.f32.bf16.bf16.f32 {%0, %1, %2, %3}, {%4, %5, %6, %7}, {%8, %9}, {%0, %1, %2, %3};"
                 : "+f"(c[0]), "+f"(c[1]), "+f"(c[2]), "+f"(c[3])
                 : "r"(a[0]), "r"(a[1]), "r"(a[2]), "r"(a[3]), "r"(b0), "r"(b1));
}
__device__ __forceinline__ uint32_t movm_t(uint32_t a) {
    uint32_t d;
    asm volatile("movmatrix.sync.aligned.m8n8.trans.b16 %0, %1;" : "=r"(d) : "r"(a));
    return d;
}
__device__ __forceinline__ uint32_t pack_bf16(float lo, float hi) {
    uint32_t d;
    asm("cvt.rn.bf16x2.f32 %0, %1, %2;" : "=r"(d) : "f"(hi), "f"(lo));
    return d;
}
__device__ __forceinline__ float bf_lo(uint32_t v) { return __uint_as_float(v << 16); }
__device__ __forceinline__ float bf_hi(uint32_t v) { return __uint_as_float(v & 0xffff0000u); }
__device__ __forceinline__ float rbf(float x) { return __uint_as_float(pack_bf16(0.f, x)); }
__device__ __forceinline__ uint32_t max_bf16x2(uint32_t a, uint32_t b) {
    uint32_t d;
    asm("max.bf16x2 %0, %1, %2;" : "=r"(d) : "r"(a), "r"(b));
    return d;
}
__device__ __forceinline__ uint32_t sub_bf16x2(uint32_t a, uint32_t b) {
    uint32_t d;
    asm("sub.rn.bf16x2 %0, %1, %2;" : "=r"(d) : "r"(a), "r"(b));
    return d;
}
__device__ __forceinline__ float ex2(float x) {
    float y;
    asm("ex2.approx.ftz.f32 %0, %1;" : "=f"(y) : "f"(x));
    return y;
}
__device__ __forceinline__ float rcp(float x) {
    float y;
    asm("rcp.approx.ftz.f32 %0, %1;" : "=f"(y) : "f"(x));
    return y;
}
__device__ __forceinline__ void red_bf16x2(__nv_bfloat16* p, uint32_t v) {
    asm volatile("red.relaxed.gpu.global.add.noftz.bf16x2 [%0], %1;" ::"l"(p), "r"(v) : "memory");
}
__device__ __forceinline__ bool elect_one() {
    uint32_t p;
    asm volatile("{\n.reg .pred P;\nelect.sync _|P, 0xffffffff;\nselp.u32 %0, 1, 0, P;\n}" : "=r"(p));
    return p;
}
__device__ __forceinline__ uint32_t timer_ns() {
    uint32_t t;
    asm volatile("mov.u32 %0, %%globaltimer_lo;" : "=r"(t));
    return t;
}
__device__ __forceinline__ void bar_all() { asm volatile("barrier.sync 2, 320;" ::: "memory"); }
__device__ __forceinline__ void bar_compute() { asm volatile("barrier.sync 1, 256;" ::: "memory"); }

struct Cursor {
    int slot = 0;
    uint32_t phase = 0;
    __device__ __forceinline__ void adv(int n) { slot += n; if (slot >= STAGES) { slot -= STAGES; phase ^= 1u; } }
};

constexpr float LOG2E = 1.4426950408889634f;

__device__ __forceinline__ void load_w(uint32_t (&a)[8][4], uint32_t addr) {
#pragma unroll
    for (int ks = 0; ks < 8; ks++) ldsm4t(a[ks], addr + ks * 2048);
}
__device__ __forceinline__ void load_act(uint32_t (&b)[4][4], uint32_t addr) {
#pragma unroll
    for (int i = 0; i < 4; i++) ldsm4(b[i], addr + i * 64);
}
__device__ __forceinline__ void mma_stage(float (&acc)[4][4], const uint32_t (&a)[8][4], const uint32_t (&b)[4][4]) {
#pragma unroll
    for (int ks = 0; ks < 8; ks++) mma16816(acc[ks & 3], a[ks], b[ks >> 1][2 * (ks & 1)], b[ks >> 1][2 * (ks & 1) + 1]);
}
__device__ __forceinline__ bool mbar_test_cluster(uint32_t bar) {
    uint32_t ok;
    asm volatile("{\n.reg .pred p;\nmbarrier.test_wait.parity.relaxed.cluster.shared::cta.b64 p, [%1], 0;\nselp.u32 %0, 1, 0, p;\n}"
                 : "=r"(ok) : "r"(bar) : "memory");
    return ok;
}

__global__ void __cluster_dims__(8, 1, 1) __launch_bounds__(THREADS, 1)
fused_decode_kernel(const void* wq, const __nv_bfloat16* __restrict__ x, __nv_bfloat16* __restrict__ out, const int shift,
                    const uint32_t tau, const uint32_t tau2, const __grid_constant__ Maps maps,
                    const __nv_bfloat16* __restrict__ b1, const __nv_bfloat16* __restrict__ b2) {
    extern __shared__ __align__(1024) uint8_t smem_raw[];
    uint32_t sb;
    asm volatile("{\n.reg .u64 a;\ncvta.to.shared.u64 a, %1;\ncvt.u32.u64 %0, a;\n}" : "=r"(sb) : "l"(smem_raw));
    uint8_t* sp = smem_raw;
    const uint32_t bar_full = sb + SM_BAR, bar_empty = bar_full + 8 * STAGES;
    const uint32_t bar_ok = bar_empty + 8 * STAGES, bar_q = bar_ok + 8, bar_o = bar_q + 8, bar_gate = bar_o + 16;

    if (threadIdx.x == 0 && blockIdx.x < N_ATT)
        asm volatile("cp.async.bulk.prefetch.L2.global [%0], %1;"
                     ::"l"(reinterpret_cast<const char*>(wq) + (size_t)blockIdx.x * PREF_BYTES), "r"(PREF_BYTES) : "memory");
    const int warp_id = __shfl_sync(0xffffffffu, (int)(threadIdx.x >> 5), 0), lane = threadIdx.x & 31;
    const int cta = (int)blockIdx.x >= shift ? blockIdx.x - shift : blockIdx.x + N_ATT;
    const bool is_att = cta < N_ATT;
    const int hkv = cta >> 3, rank = cta & 7;

    if (warp_id == 0) {
        const bool leader = elect_one();
        uint64_t pol;
        asm volatile("createpolicy.fractional.L2::evict_first.b64 %0, 1.0;" : "=l"(pol));
        const int nt = is_att ? NT_ATT : rank < N_FFN ? NT_FFN : 0;
        const int row0 = (rank * HKV + hkv) * SK - 128;
        auto coords = [&](int i, int& mi, int& c1, int& c2) {
            c2 = 0;
            if (is_att) {
                mi = (i >> 1) & 1; c1 = row0 + (i >> 2) * 128 + (i & 1) * 64;
                if (i >= NT_ATT - 12) { mi = ((i >> 3) & 1) ^ 1; c1 = row0 + 128 + SK - 256 + (i & 3) * 64; }
                if (i < 4) { mi = 2; c1 = 128 * i; c2 = cta; }
                if (i >= NT_ATT - 4) { mi = 3; c1 = 512 * hkv + 128 * (i - (NT_ATT - 4)); c2 = rank; }
            } else {
                mi = 5; c1 = FS * rank + 16 * (i - 16);
                if (i < 16) { mi = 4; c1 = 32 * i; c2 = 4 * rank; }
            }
        };
#pragma unroll
        for (int i = 0; i < D_START; i++)
            if (leader) mbar_init(bar_full + 8 * i, 1);
        if (nt > 0) {
#pragma unroll
            for (int i = 0; i < D_START; i++) {
                int mi, c1, c2;
                coords(i, mi, c1, c2);
                if (leader) {
                    mbar_expect_tx(bar_full + 8 * i, STAGE_BYTES);
                    tma3d(sb + SM_RING + i * STAGE_BYTES, &maps.m[mi], bar_full + 8 * i, c1, c2, pol);
                }
            }
        }
        const uint32_t t0 = timer_ns();
        __syncwarp();
        bar_all();
        if (is_att) cluster_arrive();
        Cursor cur, lag, hi;
        cur.slot = D_START;
        lag.slot = D_START - D_MIN;
        const uint32_t step = is_att ? tau : tau * FFN_PACE / 16;
        uint32_t due = t0 + step * PACE_OFF / 16;
#pragma unroll 1
        for (int i = D_START; i < nt; i++) {
            int mi, c1, c2;
            coords(i, mi, c1, c2);
            const CUtensorMap* map = &maps.m[mi];
            const uint32_t dst = sb + SM_RING + cur.slot * STAGE_BYTES, bar = bar_full + 8 * cur.slot;
            const uint32_t lbar = is_att ? bar_full + 8 * lag.slot : bar_q, lph = is_att ? lag.phase : 0u;
            if (i >= STAGES) mbar_wait(bar + 8 * STAGES, cur.phase ^ 1u);
            if (leader) mbar_expect_tx(bar, STAGE_BYTES);
            int it = 0;
#pragma unroll 1
            while (!mbar_test(lbar, lph) && (int)(timer_ns() - due) < 0 && ++it < 4096) {}
            if (leader) tma3d(dst, map, bar, c1, c2, pol);
            if (i == I_GATE && leader) mbar_arrive(bar_gate);
            lag.adv(i == NT_ATT - 5 ? 1 + D_MIN - D_WO : 1);
            cur.adv(1);
            due += i >= I_FAST ? tau2 : step;
            if (i == NT_ATT - 5) due += step * WO_GAP / 16;
            if (i >= D_HI) {
                if (!mbar_test(bar_full + 8 * hi.slot, hi.phase)) due += step * SLIP / 16;
                hi.adv(1);
            }
        }
    } else if (warp_id == 1) {
        if (elect_one()) {
            if (sb & 1023u) __trap();
#pragma unroll
            for (int s = D_START; s < STAGES; s++) mbar_init(bar_full + 8 * s, 1);
#pragma unroll
            for (int s = 0; s < STAGES; s++) mbar_init(bar_empty + 8 * s, is_att ? 4 : 8);
            mbar_init(bar_ok, 1);
            mbar_init(bar_q, 1);
            mbar_init(bar_o, 1);
            mbar_init(bar_o + 8, 1);
            mbar_init(bar_gate, 1);
            asm volatile("fence.mbarrier_init.release.cluster;" ::: "memory");
            mbar_expect_tx(bar_q, 1024);
            mbar_expect_tx(bar_o, 7 * 512);
            mbar_expect_tx(bar_o + 8, 7 * 512);
        }
        __syncwarp();
        bar_all();
        if (is_att) {
            cluster_arrive();
            mbar_wait(bar_gate, 0);
            if (lane == 0) {
                int it = 0;
                while (true) {
                    unsigned v;
                    asm volatile("ld.acquire.gpu.global.u32 %0, [%1];" : "=r"(v) : "l"(&g_ctr) : "memory");
                    if (v >= 8u) break;
                    __nanosleep(200);
                    if (++it > SPIN_LIMIT) __trap();
                }
            }
            __syncwarp();
            const int g = lane >> 2, t = lane & 3;
#pragma unroll 2
            for (int mt = 0; mt < 4; mt++) {
                const int col = rank * 64 + mt * 16 + g;
                float y[4] = {}, res[4];
#pragma unroll
                for (int i = 0; i < N_FFN; i++) {
                    const float4 v = __ldcg(g_gp + ((i * 8 + rank) * 4 + mt) * 32 + lane);
                    y[0] += v.x; y[1] += v.y; y[2] += v.z; y[3] += v.w;
                }
#pragma unroll
                for (int c = 0; c < 4; c++) {
                    const int cc = col + 8 * (c >> 1), bb = 2 * t + (c & 1);
                    const float z = rbf(rbf(y[c]) + __bfloat162float(b2[cc]));
                    y[c] = rbf(__fdividef(z, 1.0f + __expf(-z)));
                    res[c] = bb == hkv ? __bfloat162float(x[bb * DM + cc]) : 0.f;
                }
                *reinterpret_cast<float4*>(sp + SM_GATE + mt * 1024 + lane * 16) = make_float4(y[0], y[1], y[2], y[3]);
                *reinterpret_cast<float4*>(sp + SM_GATE + mt * 1024 + 512 + lane * 16) = make_float4(res[0], res[1], res[2], res[3]);
            }
            __syncwarp();
            if (lane == 0) {
                mbar_arrive(bar_ok);
                atomicInc(&g_ctr, N_CTA - 1);
            }
        } else if (rank == N_FFN) {
#pragma unroll 4
            for (int i = 0; i < 16; i++) reinterpret_cast<uint4*>(out)[i * 32 + lane] = make_uint4(0, 0, 0, 0);
            __syncwarp();
            if (lane == 0) {
                asm volatile("fence.acq_rel.gpu;" ::: "memory");
                atomicInc(&g_ctr, N_CTA - 1);
            }
        }
    } else {
        const int warp = warp_id - 2, tid = threadIdx.x - 64;
        const int g = lane >> 2, t = lane & 3;
        {
            uint4 xv[2];
#pragma unroll
            for (int i = 0; i < 2; i++) xv[i] = __ldg(reinterpret_cast<const uint4*>(x + warp * DM + i * 256 + lane * 8));
            bar_all();
            if (is_att) cluster_arrive();
            uint32_t w[8] = {xv[0].x, xv[0].y, xv[0].z, xv[0].w, xv[1].x, xv[1].y, xv[1].z, xv[1].w};
            float s0 = 0.f, s1 = 0.f;
#pragma unroll
            for (int i = 0; i < 8; i++) { s0 += bf_lo(w[i]); s1 += bf_hi(w[i]); }
            s0 += s1;
#pragma unroll
            for (int o = 16; o > 0; o >>= 1) s0 += __shfl_xor_sync(0xffffffffu, s0, o);
            const float mean = s0 * (1.0f / DM);
            s0 = 0.f; s1 = 0.f;
#pragma unroll
            for (int i = 0; i < 8; i++) {
                const float d0 = bf_lo(w[i]) - mean, d1 = bf_hi(w[i]) - mean;
                s0 += d0 * d0; s1 += d1 * d1;
            }
            s0 += s1;
#pragma unroll
            for (int o = 16; o > 0; o >>= 1) s0 += __shfl_xor_sync(0xffffffffu, s0, o);
            const uint32_t mb = pack_bf16(mean, mean);
            float sd;
            asm("sqrt.approx.f32 %0, %1;" : "=f"(sd) : "f"(rbf(rbf(s0 * (1.0f / DM)) + 1e-5f)));
            const float rs = rcp(rbf(sd));
#pragma unroll
            for (int i = 0; i < 8; i++) {
                const uint32_t d = sub_bf16x2(w[i], mb);
                w[i] = pack_bf16(bf_lo(d) * rs, bf_hi(d) * rs);
            }
#pragma unroll
            for (int i = 0; i < 2; i++)
                *reinterpret_cast<uint4*>(sp + SM_XN + (warp * XN_STRIDE + i * 256 + lane * 8) * 2) =
                    make_uint4(w[4 * i], w[4 * i + 1], w[4 * i + 2], w[4 * i + 3]);
        }
        bar_compute();
        const uint32_t* xn32 = reinterpret_cast<const uint32_t*>(sp + SM_XN) + g * (XN_STRIDE / 2) + t;
        const int krow = (lane & 7) + (lane >> 4) * 8;
        const int cbit = (lane >> 3) & 1;
        const int wq4 = warp & 3;
        Cursor cur;

        if (is_att) {
            cluster_wait();
            const uint32_t wbase = sb + SM_RING + krow * 128 + (((2 * wq4 + cbit) ^ (lane & 7)) << 4);
            const uint32_t abase = sb + SM_XN + (lane & 7) * (XN_STRIDE * 2) + (lane >> 3) * 16;
            if (warp < 4) {
                float acc[4][4] = {};
#pragma unroll 1
                for (int s = 0; s < 4; s++) {
                    uint32_t a[8][4], bf[4][4];
                    load_act(bf, abase + s * 256);
                    mbar_wait(bar_full + 8 * s, 0);
                    load_w(a, wbase + s * STAGE_BYTES);
                    mma_stage(acc, a, bf);
                    __syncwarp();
                    if (lane == 0) mbar_arrive(bar_empty + 8 * s);
                }
                const uint32_t q0 = movm_t(pack_bf16((acc[0][0] + acc[1][0]) + (acc[2][0] + acc[3][0]), (acc[0][1] + acc[1][1]) + (acc[2][1] + acc[3][1])));
                const uint32_t q1 = movm_t(pack_bf16((acc[0][2] + acc[1][2]) + (acc[2][2] + acc[3][2]), (acc[0][3] + acc[1][3]) + (acc[2][3] + acc[3][3])));
                st_async2(mapa(sb + SM_QIN + ((rank * 4 + warp) * 4 + t) * 8, g), q0, q1, mapa(bar_q, g));
            }
            uint2 qf[8];
            mbar_wait_cluster(bar_q, 0);
#pragma unroll
            for (int kk = 0; kk < 8; kk++) qf[kk] = *reinterpret_cast<const uint2*>(sp + SM_QIN + (((g & 3) * 8 + kk) * 4 + t) * 8);
            float o[8][4] = {};
            uint32_t mpk = 0xff7fff7fu;
            float m0 = bf_lo(mpk), m1 = bf_hi(mpk), l0 = 0.f, l1 = 0.f;
            uint32_t koff[4], voff[4];
#pragma unroll
            for (int i = 0; i < 4; i++) {
                koff[i] = (16 * wq4 + (lane & 7) + cbit * 8) * 128 + (((2 * i + (lane >> 4)) ^ (lane & 7)) << 4);
                voff[i] = (16 * wq4 + krow) * 128 + (((2 * i + cbit) ^ (lane & 7)) << 4);
            }
            uint32_t s01, s23, u01 = 0, u23 = 0;
            cur.adv(4 + (warp >> 2));
#pragma unroll 1
            for (int tile = 0;; tile++) {
                const bool last = tile >= KV_TILES / 2 - 2;
                if (tile == KV_TILES / 2 - 3) mbar_wait(bar_ok, 0);
                const uint32_t kbar = bar_full + 8 * cur.slot, vbar = kbar + 16;
                const uint32_t kb = sb + SM_RING + cur.slot * STAGE_BYTES, vb = kb + 2 * STAGE_BYTES;
                uint32_t a[8][4];
                mbar_wait(kbar, cur.phase);
#pragma unroll
                for (int i = 0; i < 8; i++) ldsm4(a[i], kb + (i >> 2) * 8192 + koff[i & 3]);
                const bool early = __all_sync(0xffffffffu, !last && mbar_test(vbar, cur.phase));
                float sa[4][4] = {};
#pragma unroll
                for (int i = 0; i < 8; i++) mma16816(sa[i & 3], a[i], qf[i].x, qf[i].y);
                __syncwarp();
                if (lane == 0) mbar_arrive(kbar + 8 * STAGES);
                if (early) {
#pragma unroll
                    for (int i = 0; i < 8; i++) ldsm4t(a[i], vb + (i >> 2) * 8192 + voff[i & 3]);
                }
                s01 = pack_bf16((sa[0][0] + sa[1][0]) + (sa[2][0] + sa[3][0]), (sa[0][1] + sa[1][1]) + (sa[2][1] + sa[3][1]));
                s23 = pack_bf16((sa[0][2] + sa[1][2]) + (sa[2][2] + sa[3][2]), (sa[0][3] + sa[1][3]) + (sa[2][3] + sa[3][3]));
                const float scale = 0.08838834764831845f;
                s01 = pack_bf16(bf_lo(s01) * scale, bf_hi(s01) * scale);
                s23 = pack_bf16(bf_lo(s23) * scale, bf_hi(s23) * scale);
                if (last) {
                    if (tile == KV_TILES / 2 - 1) break;
                    u01 = s01; u23 = s23;
                    cur.adv(2);
                    continue;
                }
                uint32_t mx = max_bf16x2(max_bf16x2(s01, s23), mpk);
                if (__any_sync(0xffffffffu, mx != mpk)) {
                    mx = max_bf16x2(mx, __shfl_xor_sync(0xffffffffu, mx, 4));
                    mx = max_bf16x2(mx, __shfl_xor_sync(0xffffffffu, mx, 8));
                    mx = max_bf16x2(mx, __shfl_xor_sync(0xffffffffu, mx, 16));
                    const float n0 = bf_lo(mx), n1 = bf_hi(mx);
                    const float a0 = ex2((m0 - n0) * LOG2E), a1 = ex2((m1 - n1) * LOG2E);
                    m0 = n0; m1 = n1; mpk = mx;
                    l0 *= a0; l1 *= a1;
#pragma unroll
                    for (int mt = 0; mt < 8; mt++) { o[mt][0] *= a0; o[mt][1] *= a1; o[mt][2] *= a0; o[mt][3] *= a1; }
                }
                const float p0 = ex2((bf_lo(s01) - m0) * LOG2E), p1 = ex2((bf_hi(s01) - m1) * LOG2E);
                const float p2 = ex2((bf_lo(s23) - m0) * LOG2E), p3 = ex2((bf_hi(s23) - m1) * LOG2E);
                l0 += p0 + p2; l1 += p1 + p3;
                const uint32_t pb0 = movm_t(pack_bf16(p0, p1)), pb1 = movm_t(pack_bf16(p2, p3));
                if (!early) {
                    mbar_wait(vbar, cur.phase);
#pragma unroll
                    for (int i = 0; i < 8; i++) ldsm4t(a[i], vb + (i >> 2) * 8192 + voff[i & 3]);
                }
#pragma unroll
                for (int i = 0; i < 8; i++) mma16816(o[i], a[i], pb0, pb1);
                __syncwarp();
                if (lane == 0) mbar_arrive(vbar + 8 * STAGES);
                cur.adv(4);
            }
            constexpr int SLOT_K = (NT_ATT - 12) % STAGES, SLOT_V = SLOT_K + 4;
            static_assert(SLOT_V + 4 <= STAGES, "last tiles must not wrap");
            constexpr uint32_t PH_LAST = ((NT_ATT - 12) / STAGES) & 1;
            const uint32_t orow = sb + SM_XN + rank * (XN_STRIDE * 2);
            const bool hi = t >= 2;
            {
                uint32_t mx = max_bf16x2(max_bf16x2(max_bf16x2(s01, s23), max_bf16x2(u01, u23)), mpk);
                mx = max_bf16x2(mx, __shfl_xor_sync(0xffffffffu, mx, 4));
                mx = max_bf16x2(mx, __shfl_xor_sync(0xffffffffu, mx, 8));
                mx = max_bf16x2(mx, __shfl_xor_sync(0xffffffffu, mx, 16));
                if (lane < 2) sts32(sb + SM_ML + lane * 32 + warp * 4, mx);
                bar_compute();
                const uint4 ma = lds128(sb + SM_ML + (t & 1) * 32), mb = lds128(sb + SM_ML + (t & 1) * 32 + 16);
                const uint32_t M = max_bf16x2(max_bf16x2(max_bf16x2(ma.x, ma.y), max_bf16x2(ma.z, ma.w)),
                                              max_bf16x2(max_bf16x2(mb.x, mb.y), max_bf16x2(mb.z, mb.w)));
                const float M0 = bf_lo(M), M1 = bf_hi(M);
                const float f0 = ex2((m0 - M0) * LOG2E), f1 = ex2((m1 - M1) * LOG2E);
                l0 *= f0; l1 *= f1;
#pragma unroll
                for (int j = 0; j < 2; j++) {
                    const uint32_t a01 = j ? s01 : u01, a23 = j ? s23 : u23;
                    const float p0 = ex2((bf_lo(a01) - M0) * LOG2E), p1 = ex2((bf_hi(a01) - M1) * LOG2E);
                    const float p2 = ex2((bf_lo(a23) - M0) * LOG2E), p3 = ex2((bf_hi(a23) - M1) * LOG2E);
                    l0 += p0 + p2; l1 += p1 + p3;
                    const uint32_t pb0 = movm_t(pack_bf16(p0, p1)), pb1 = movm_t(pack_bf16(p2, p3));
                    if (lane < 16) *reinterpret_cast<uint2*>(sp + SM_H + lane * 144 + (warp >> 2) * 64 + j * 32 + wq4 * 8) = make_uint2(pb0, pb1);
                }
                uint8_t* part = sp + SM_RING + (SLOT_K + (warp >> 2)) * STAGE_BYTES + wq4 * 2048 + (t >> 1) * 1024 +
                                ((2 * g + (t & 1)) ^ (4 * ((t >> 1) ^ (warp >> 2)))) * 16;
#pragma unroll
                for (int i = 0; i < 4; i++)
                    *reinterpret_cast<float4*>(part + i * 256) =
                        make_float4((hi ? o[4 + i][0] : o[i][0]) * f0, (hi ? o[4 + i][1] : o[i][1]) * f1,
                                    (hi ? o[4 + i][2] : o[i][2]) * f0, (hi ? o[4 + i][3] : o[i][3]) * f1);
#pragma unroll
                for (int of = 4; of < 32; of <<= 1) {
                    l0 += __shfl_xor_sync(0xffffffffu, l0, of);
                    l1 += __shfl_xor_sync(0xffffffffu, l1, of);
                }
                if (lane < 2) *reinterpret_cast<float2*>(sp + SM_ML + 64 + lane * 64 + warp * 8) = make_float2(l0, l1);
            }
            bar_compute();
            {
                uint4 pf[4];
#pragma unroll
                for (int i = 0; i < 4; i++) pf[i] = *reinterpret_cast<const uint4*>(sp + SM_H + (lane & 15) * 144 + (lane >> 4) * 64 + i * 16);
                const uint8_t* psum = sp + SM_RING + (SLOT_K + (t >> 1)) * STAGE_BYTES + warp * 256 +
                                      ((2 * g + (t & 1)) ^ (4 * ((t >> 1) ^ (warp >> 2)))) * 16;
                float acc[4][4];
#pragma unroll
                for (int w = 0; w < 4; w++) {
                    const float4 v = *reinterpret_cast<const float4*>(psum + w * 2048);
                    acc[w][0] = v.x; acc[w][1] = v.y; acc[w][2] = v.z; acc[w][3] = v.w;
                }
                float L0 = 0.f, L1 = 0.f;
#pragma unroll
                for (int i = 0; i < 4; i++) {
                    const float4 v = *reinterpret_cast<const float4*>(sp + SM_ML + 64 + (t & 1) * 64 + i * 16);
                    L0 += v.x + v.z; L1 += v.y + v.w;
                }
                const float i0 = rcp(L0), i1 = rcp(L1);
                const uint32_t vbase = wbase + SLOT_V * STAGE_BYTES + (warp >> 2) * 8192;
                const uint32_t ost = orow + (g & 3) * 256 + warp * 32 + (g >> 2) * 16 + t * 4;
#pragma unroll
                for (int j = 0; j < 4; j++) {
                    uint32_t a[4][4];
                    const bool on = (lane >> 4) == (j & 1);
                    const uint4 pa = pf[j & 2], pb = pf[(j & 2) + 1];
                    mbar_wait(bar_full + 8 * (SLOT_V + j), PH_LAST);
#pragma unroll
                    for (int ks = 0; ks < 4; ks++) ldsm4t(a[ks], vbase + j * STAGE_BYTES + ks * 2048);
                    mma16816(acc[0], a[0], on ? pa.x : 0u, on ? pa.y : 0u);
                    mma16816(acc[1], a[1], on ? pa.z : 0u, on ? pa.w : 0u);
                    mma16816(acc[2], a[2], on ? pb.x : 0u, on ? pb.y : 0u);
                    mma16816(acc[3], a[3], on ? pb.z : 0u, on ? pb.w : 0u);
                }
#pragma unroll
                for (int c = 0; c < 4; c++) { acc[0][c] += acc[2][c]; acc[1][c] += acc[3][c]; }
                const float c0 = acc[0][0] + acc[1][0], c1 = acc[0][1] + acc[1][1], c2 = acc[0][2] + acc[1][2], c3 = acc[0][3] + acc[1][3];
                const float r0 = (hi ? c2 : c0) + __shfl_xor_sync(0xffffffffu, hi ? c0 : c2, 2);
                const float r1 = (hi ? c3 : c1) + __shfl_xor_sync(0xffffffffu, hi ? c1 : c3, 2);
                sts32(ost, movm_t(pack_bf16(r0 * i0, r1 * i1)));
            }
            bar_compute();
            if (warp != rank) {
                const uint4 u0 = lds128(orow + lane * 16), u1 = lds128(orow + lane * 16 + 512);
                const uint32_t odst = mapa(orow + lane * 16, warp), obar = mapa(bar_o, warp);
                st_async4(odst, u0, obar);
                st_async4(odst + 512, u1, obar + 8);
            }
            if (warp < 4) {
                __nv_bfloat16* dst = out + __shfl_sync(0xffffffffu, g * DM + rank * 64 + warp * 16 + 2 * t, lane);
                constexpr uint32_t ph = ((NT_ATT - 4) / STAGES) & 1;
                static_assert((NT_ATT - 4) % STAGES == 0, "wo must start in slot 0");
                uint32_t a[4][8][4], bf[4][4][4];
                float acc[4][4] = {};
                mbar_wait(bar_full, ph);
                load_w(a[0], wbase);
                bool w1;
                int it = 0;
#pragma unroll 1
                while (!(w1 = __all_sync(0xffffffffu, mbar_test(bar_full + 8, ph))) && !__all_sync(0xffffffffu, mbar_test_cluster(bar_o)))
                    if (++it > SPIN_LIMIT) __trap();
                if (w1) load_w(a[1], wbase + STAGE_BYTES);
                mbar_wait_cluster(bar_o, 0);
                load_act(bf[0], abase);
                load_act(bf[1], abase + 256);
                mbar_wait_cluster(bar_o + 8, 0);
                load_act(bf[2], abase + 512);
                load_act(bf[3], abase + 768);
                if (!w1) mbar_wait(bar_full + 8, ph);
                const bool w2 = __all_sync(0xffffffffu, mbar_test(bar_full + 16, ph)), w3 = __all_sync(0xffffffffu, mbar_test(bar_full + 24, ph));
                if (!w1) load_w(a[1], wbase + STAGE_BYTES);
                mma_stage(acc, a[0], bf[0]);
                if (w2) load_w(a[2], wbase + 2 * STAGE_BYTES);
                mma_stage(acc, a[1], bf[1]);
                if (!w2) { mbar_wait(bar_full + 16, ph); load_w(a[2], wbase + 2 * STAGE_BYTES); }
                if (w3) load_w(a[3], wbase + 3 * STAGE_BYTES);
                mma_stage(acc, a[2], bf[2]);
                if (!w3) { mbar_wait(bar_full + 24, ph); load_w(a[3], wbase + 3 * STAGE_BYTES); }
                mma_stage(acc, a[3], bf[3]);
                float r[4];
                const uint4 gt = lds128(sb + SM_GATE + warp * 1024 + lane * 16), rs = lds128(sb + SM_GATE + warp * 1024 + 512 + lane * 16);
#pragma unroll
                for (int c = 0; c < 4; c++) r[c] = (acc[0][c] + acc[1][c]) + (acc[2][c] + acc[3][c]);
                red_bf16x2(dst, movm_t(pack_bf16(fmaf(r[0], __uint_as_float(gt.x), __uint_as_float(rs.x)),
                                                 fmaf(r[1], __uint_as_float(gt.y), __uint_as_float(rs.y)))));
                red_bf16x2(dst + 8, movm_t(pack_bf16(fmaf(r[2], __uint_as_float(gt.z), __uint_as_float(rs.z)),
                                                     fmaf(r[3], __uint_as_float(gt.w), __uint_as_float(rs.w)))));
            }
        } else if (rank < N_FFN) {
            if (tid < FS / 8) *reinterpret_cast<uint4*>(sp + SM_QIN + tid * 16) = __ldg(reinterpret_cast<const uint4*>(b1 + FS * rank) + tid);
            float acc[4][4] = {};
#pragma unroll 1
            for (int kt = 0; kt < 16; kt++) {
                mbar_wait(bar_full + 8 * cur.slot, cur.phase);
                const uint32_t base = sb + SM_RING + cur.slot * STAGE_BYTES + (warp >> 1) * 4096 + krow * 128;
#pragma unroll
                for (int ks = 0; ks < 2; ks++) {
                    const uint32_t b0 = xn32[kt * 16 + ks * 8], b1r = xn32[kt * 16 + ks * 8 + 4];
#pragma unroll
                    for (int mt = 0; mt < 2; mt++) {
                        uint32_t a[4];
                        ldsm4t(a, base + ks * 2048 + (((4 * (warp & 1) + 2 * mt + cbit) ^ (lane & 7)) << 4));
                        mma16816(acc[mt], a, b0, b1r);
                    }
                }
                __syncwarp();
                if (lane == 0) mbar_arrive(bar_empty + 8 * cur.slot);
                cur.adv(1);
            }
            bar_compute();
            __nv_bfloat16* hs = reinterpret_cast<__nv_bfloat16*>(sp + SM_H);
            const __nv_bfloat16* b1s = reinterpret_cast<const __nv_bfloat16*>(sp + SM_QIN);
#pragma unroll
            for (int mt = 0; mt < 2; mt++)
#pragma unroll
                for (int c = 0; c < 4; c++) {
                    const int u = warp * 32 + mt * 16 + g + (c >> 1) * 8;
                    const float hv = rbf(rbf(acc[mt][c]) + __bfloat162float(b1s[u]));
                    const float inner = 0.7978845608028654f * (hv + 0.044715f * hv * hv * hv);
                    hs[(2 * t + (c & 1)) * H_STRIDE + u] = __float2bfloat16_rn(0.5f * hv * (1.0f + tanhf(inner)));
                    acc[mt][c] = 0.f;
                }
            bar_compute();
            const uint32_t* h32 = reinterpret_cast<const uint32_t*>(sp + SM_H) + g * (H_STRIDE / 2) + t;
#pragma unroll 1
            for (int kt = 0; kt < 16; kt++) {
                const uint32_t b0 = h32[kt * 8], b1r = h32[kt * 8 + 4];
                mbar_wait(bar_full + 8 * cur.slot, cur.phase);
                const uint32_t base = sb + SM_RING + cur.slot * STAGE_BYTES + warp * 2048 + krow * 128;
#pragma unroll
                for (int mt = 0; mt < 4; mt++) {
                    uint32_t a[4];
                    ldsm4t(a, base + (((2 * mt + cbit) ^ (lane & 7)) << 4));
                    mma16816(acc[mt], a, b0, b1r);
                }
                __syncwarp();
                if (lane == 0) mbar_arrive(bar_empty + 8 * cur.slot);
                cur.adv(1);
            }
#pragma unroll
            for (int mt = 0; mt < 4; mt++)
                g_gp[((rank * 8 + warp) * 4 + mt) * 32 + lane] = make_float4(acc[mt][0], acc[mt][1], acc[mt][2], acc[mt][3]);
            bar_compute();
            if (tid == 0) {
                asm volatile("fence.acq_rel.gpu;" ::: "memory");
                atomicInc(&g_ctr, N_CTA - 1);
            }
        }
    }
}

typedef CUresult (*EncodeTiledFn)(CUtensorMap*, CUtensorMapDataType, cuuint32_t, void*, const cuuint64_t*, const cuuint64_t*,
                                  const cuuint32_t*, const cuuint32_t*, CUtensorMapInterleave, CUtensorMapSwizzle,
                                  CUtensorMapL2promotion, CUtensorMapFloatOOBfill);

void encode(EncodeTiledFn fn, CUtensorMap* m, const void* ptr, int rows, int cols, int nrow, int nblk, CUtensorMapL2promotion promo) {
    const cuuint64_t dims[3] = {64, (cuuint64_t)rows, (cuuint64_t)cols / 64}, strides[2] = {(cuuint64_t)cols * 2, 128};
    const cuuint32_t box[3] = {64, (cuuint32_t)nrow, (cuuint32_t)nblk}, es[3] = {1, 1, 1};
    fn(m, CU_TENSOR_MAP_DATA_TYPE_BFLOAT16, 3, const_cast<void*>(ptr), dims, strides, box, es,
       CU_TENSOR_MAP_INTERLEAVE_NONE, CU_TENSOR_MAP_SWIZZLE_128B, promo, CU_TENSOR_MAP_FLOAT_OOB_FILL_NONE);
}

}

extern "C" void kernel_launch(void* const* d_in, const int* in_sizes, int n_in, void* d_out, int out_size) {
    (void)in_sizes; (void)n_in; (void)out_size;
    EncodeTiledFn fn = nullptr;
    cudaDriverEntryPointQueryResult qr;
    cudaGetDriverEntryPoint("cuTensorMapEncodeTiled", (void**)&fn, cudaEnableDefault, &qr);
    cudaFuncSetAttribute(fused_decode_kernel, cudaFuncAttributeMaxDynamicSharedMemorySize, SMEM_BYTES);

    int dev = 0, khz = 0, bits = 0;
    cudaGetDevice(&dev);
    cudaDeviceGetAttribute(&khz, cudaDevAttrMemoryClockRate, dev);
    cudaDeviceGetAttribute(&bits, cudaDevAttrGlobalMemoryBusWidth, dev);
    const double rel = (khz > 0 && bits > 0) ? (2619000.0 * 5120.0) / ((double)khz * bits) : 1.0;
    const uint32_t tau = (uint32_t)(TAU_NS * rel + 0.5), tau2 = (uint32_t)(TAU2_NS * rel + 0.5);

    int nclusters = 0;
    {
        cudaLaunchConfig_t cfg = {};
        cfg.gridDim = dim3(N_CTA); cfg.blockDim = dim3(THREADS); cfg.dynamicSmemBytes = SMEM_BYTES;
        cudaLaunchAttribute at;
        at.id = cudaLaunchAttributeClusterDimension;
        at.val.clusterDim.x = 8; at.val.clusterDim.y = 1; at.val.clusterDim.z = 1;
        cfg.attrs = &at; cfg.numAttrs = 1;
        if (cudaOccupancyMaxActiveClusters(&nclusters, fused_decode_kernel, &cfg) != cudaSuccess) { nclusters = 0; cudaGetLastError(); }
    }
    const int shift = nclusters >= N_CTA / 8 ? 0 : 8;

    Maps maps;
    encode(fn, &maps.m[0], d_in[1], NB * HKV * SK, DH, 64, 2, CU_TENSOR_MAP_L2_PROMOTION_L2_256B);
    encode(fn, &maps.m[1], d_in[2], NB * HKV * SK, DH, 64, 2, CU_TENSOR_MAP_L2_PROMOTION_L2_256B);
    encode(fn, &maps.m[2], d_in[3], DM, HQ * DH, 128, 1, CU_TENSOR_MAP_L2_PROMOTION_L2_128B);
    encode(fn, &maps.m[3], d_in[4], HQ * DH, DM, 128, 1, CU_TENSOR_MAP_L2_PROMOTION_L2_128B);
    encode(fn, &maps.m[4], d_in[6], DM, FF, 32, 4, CU_TENSOR_MAP_L2_PROMOTION_L2_256B);
    encode(fn, &maps.m[5], d_in[8], FF, DM, 16, 8, CU_TENSOR_MAP_L2_PROMOTION_L2_256B);
    fused_decode_kernel<<<N_CTA, THREADS, SMEM_BYTES>>>(d_in[3], (const __nv_bfloat16*)d_in[0], (__nv_bfloat16*)d_out, shift, tau, tau2,
                                                        maps, (const __nv_bfloat16*)d_in[7], (const __nv_bfloat16*)d_in[9]);
}
```

```cpp
#include <cuda_runtime.h>
#include <cuda_bf16.h>
#include <cuda.h>
#include <stdint.h>

namespace {

constexpr int NB = 8, DM = 512, HQ = 32, HKV = 8, SK = 4096, DH = 128, FF = 1792;
constexpr int N_ATT = 64, N_FFN = 7, N_CTA = 72;
constexpr int THREADS = 320;
constexpr int STAGES = 12;
constexpr int TAU_NS = 329, TAU2_NS = 320;
constexpr int I_FAST = 92;
constexpr int D_START = 4;
constexpr int PACE_OFF = 36;
constexpr int D_MIN = 4, D_WO = 3;
constexpr int D_HI = 6, SLIP = 1;
constexpr int WO_GAP = 16;
constexpr int FFN_PACE = 48;
constexpr int I_GATE = 104;
constexpr int PREF_BYTES = 16384;
constexpr int STAGE_BYTES = 16384;
constexpr int KV_TILES = 64;
constexpr int NT_ATT = 4 + 2 * KV_TILES + 4;
constexpr int FS = 256;
constexpr int NT_FFN = 32;
constexpr int XN_STRIDE = DM + 8;
constexpr int H_STRIDE = FS + 8;

constexpr int SM_RING = 0;
constexpr int SM_XN = SM_RING + STAGES * STAGE_BYTES;
constexpr int SM_QIN = SM_XN + NB * XN_STRIDE * 2;
constexpr int SM_ML = SM_QIN + 1024;
constexpr int SM_H = SM_ML + 256;
constexpr int SM_GATE = SM_H + NB * H_STRIDE * 2;
constexpr int SM_BAR = SM_GATE + 4096;
constexpr int SMEM_BYTES = SM_BAR + (2 * STAGES + 6) * 8;
static_assert(SMEM_BYTES <= 232448, "smem");
static_assert(SM_QIN % 16 == 0 && SM_BAR % 8 == 0, "align");

__device__ float4 g_gp[N_FFN * 8 * 4 * 32];
__device__ unsigned g_ctr;

constexpr int SPIN_LIMIT = 1 << 22;

struct Maps { CUtensorMap m[6]; };

__device__ __forceinline__ void mbar_init(uint32_t bar, uint32_t cnt) {
    asm volatile("mbarrier.init.shared::cta.b64 [%0], %1;" ::"r"(bar), "r"(cnt) : "memory");
}
__device__ __forceinline__ void mbar_expect_tx(uint32_t bar, uint32_t bytes) {
    asm volatile("mbarrier.arrive.expect_tx.shared::cta.b64 _, [%0], %1;" ::"r"(bar), "r"(bytes) : "memory");
}
__device__ __forceinline__ void mbar_arrive(uint32_t bar) {
    asm volatile("mbarrier.arrive.shared::cta.b64 _, [%0];" ::"r"(bar) : "memory");
}
__device__ __forceinline__ void mbar_wait(uint32_t bar, uint32_t parity) {
    uint32_t ok;
    int it = 0;
    do {
        asm volatile("{\n.reg .pred p;\nmbarrier.try_wait.parity.shared::cta.b64 p, [%1], %2;\nselp.u32 %0, 1, 0, p;\n}"
                     : "=r"(ok) : "r"(bar), "r"(parity) : "memory");
        if (++it > SPIN_LIMIT) __trap();
    } while (!ok);
}
__device__ __forceinline__ void mbar_wait_cluster(uint32_t bar, uint32_t parity) {
    uint32_t ok;
    int it = 0;
    do {
        asm volatile("{\n.reg .pred p;\nmbarrier.try_wait.parity.relaxed.cluster.shared::cta.b64 p, [%1], %2;\nselp.u32 %0, 1, 0, p;\n}"
                     : "=r"(ok) : "r"(bar), "r"(parity) : "memory");
        if (++it > SPIN_LIMIT) __trap();
    } while (!ok);
    asm volatile("fence.acquire.sync_restrict::shared::cluster.cluster;" ::: "memory");
}
__device__ __forceinline__ bool mbar_test(uint32_t bar, uint32_t parity) {
    uint32_t ok;
    asm volatile("{\n.reg .pred p;\nmbarrier.test_wait.parity.shared::cta.b64 p, [%1], %2;\nselp.u32 %0, 1, 0, p;\n}"
                 : "=r"(ok) : "r"(bar), "r"(parity) : "memory");
    return ok;
}
__device__ __forceinline__ void tma3d(uint32_t dst, const CUtensorMap* m, uint32_t bar, int c1, int c2, uint64_t pol) {
    asm volatile("cp.async.bulk.tensor.3d.shared::cluster.global.mbarrier::complete_tx::bytes.L2::cache_hint [%0], [%1, {%3, %4, %5}], [%2], %6;"
                 ::"r"(dst), "l"(m), "r"(bar), "r"(0), "r"(c1), "r"(c2), "l"(pol) : "memory");
}
__device__ __forceinline__ uint32_t mapa(uint32_t addr, uint32_t rank) {
    uint32_t r;
    asm("mapa.shared::cluster.u32 %0, %1, %2;" : "=r"(r) : "r"(addr), "r"(rank));
    return r;
}
__device__ __forceinline__ void st_async2(uint32_t addr, uint32_t a, uint32_t b, uint32_t bar) {
    asm volatile("st.async.shared::cluster.mbarrier::complete_tx::bytes.v2.b32 [%0], {%1, %2}, [%3];"
                 ::"r"(addr), "r"(a), "r"(b), "r"(bar) : "memory");
}
__device__ __forceinline__ void st_async4(uint32_t addr, const uint4& v, uint32_t bar) {
    asm volatile("st.async.shared::cluster.mbarrier::complete_tx::bytes.v4.b32 [%0], {%1, %2, %3, %4}, [%5];"
                 ::"r"(addr), "r"(v.x), "r"(v.y), "r"(v.z), "r"(v.w), "r"(bar) : "memory");
}
__device__ __forceinline__ void cluster_arrive() { asm volatile("barrier.cluster.arrive.relaxed.aligned;" ::: "memory"); }
__device__ __forceinline__ void cluster_wait() { asm volatile("barrier.cluster.wait.aligned;" ::: "memory"); }
__device__ __forceinline__ void sts32(uint32_t addr, uint32_t v) {
    asm volatile("st.shared.b32 [%0], %1;" ::"r"(addr), "r"(v) : "memory");
}
__device__ __forceinline__ uint4 lds128(uint32_t addr) {
    uint4 v;
    asm volatile("ld.shared.v4.b32 {%0, %1, %2, %3}, [%4];" : "=r"(v.x), "=r"(v.y), "=r"(v.z), "=r"(v.w) : "r"(addr) : "memory");
    return v;
}
__device__ __forceinline__ void ldsm4(uint32_t (&r)[4], uint32_t addr) {
    asm volatile("ldmatrix.sync.aligned.m8n8.x4.shared.b16 {%0, %1, %2, %3}, [%4];"
                 : "=r"(r[0]), "=r"(r[1]), "=r"(r[2]), "=r"(r[3]) : "r"(addr) : "memory");
}
__device__ __forceinline__ void ldsm4t(uint32_t (&r)[4], uint32_t addr) {
    asm volatile("ldmatrix.sync.aligned.m8n8.x4.trans.shared.b16 {%0, %1, %2, %3}, [%4];"
                 : "=r"(r[0]), "=r"(r[1]), "=r"(r[2]), "=r"(r[3]) : "r"(addr) : "memory");
}
__device__ __forceinline__ void mma16816(float (&c)[4], const uint32_t (&a)[4], uint32_t b0, uint32_t b1) {
    asm volatile("mma.sync.aligned.m16n8k16.row.col.f32.bf16.bf16.f32 {%0, %1, %2, %3}, {%4, %5, %6, %7}, {%8, %9}, {%0, %1, %2, %3};"
                 : "+f"(c[0]), "+f"(c[1]), "+f"(c[2]), "+f"(c[3])
                 : "r"(a[0]), "r"(a[1]), "r"(a[2]), "r"(a[3]), "r"(b0), "r"(b1));
}
__device__ __forceinline__ uint32_t movm_t(uint32_t a) {
    uint32_t d;
    asm volatile("movmatrix.sync.aligned.m8n8.trans.b16 %0, %1;" : "=r"(d) : "r"(a));
    return d;
}
__device__ __forceinline__ uint32_t pack_bf16(float lo, float hi) {
    uint32_t d;
    asm("cvt.rn.bf16x2.f32 %0, %1, %2;" : "=r"(d) : "f"(hi), "f"(lo));
    return d;
}
__device__ __forceinline__ float bf_lo(uint32_t v) { return __uint_as_float(v << 16); }
__device__ __forceinline__ float bf_hi(uint32_t v) { return __uint_as_float(v & 0xffff0000u); }
__device__ __forceinline__ float rbf(float x) { return __uint_as_float(pack_bf16(0.f, x)); }
__device__ __forceinline__ uint32_t max_bf16x2(uint32_t a, uint32_t b) {
    uint32_t d;
    asm("max.bf16x2 %0, %1, %2;" : "=r"(d) : "r"(a), "r"(b));
    return d;
}
__device__ __forceinline__ uint32_t sub_bf16x2(uint32_t a, uint32_t b) {
    uint32_t d;
    asm("sub.rn.bf16x2 %0, %1, %2;" : "=r"(d) : "r"(a), "r"(b));
    return d;
}
__device__ __forceinline__ float ex2(float x) {
    float y;
    asm("ex2.approx.ftz.f32 %0, %1;" : "=f"(y) : "f"(x));
    return y;
}
__device__ __forceinline__ float rcp(float x) {
    float y;
    asm("rcp.approx.ftz.f32 %0, %1;" : "=f"(y) : "f"(x));
    return y;
}
__device__ __forceinline__ void red_bf16x2(__nv_bfloat16* p, uint32_t v) {
    asm volatile("red.relaxed.gpu.global.add.noftz.bf16x2 [%0], %1;" ::"l"(p), "r"(v) : "memory");
}
__device__ __forceinline__ bool elect_one() {
    uint32_t p;
    asm volatile("{\n.reg .pred P;\nelect.sync _|P, 0xffffffff;\nselp.u32 %0, 1, 0, P;\n}" : "=r"(p));
    return p;
}
__device__ __forceinline__ uint32_t timer_ns() {
    uint32_t t;
    asm volatile("mov.u32 %0, %%globaltimer_lo;" : "=r"(t));
    return t;
}
__device__ __forceinline__ void bar_all() { asm volatile("barrier.sync 2, 320;" ::: "memory"); }
__device__ __forceinline__ void bar_compute() { asm volatile("barrier.sync 1, 256;" ::: "memory"); }

struct Cursor {
    int slot = 0;
    uint32_t phase = 0;
    __device__ __forceinline__ void adv(int n) { slot += n; if (slot >= STAGES) { slot -= STAGES; phase ^= 1u; } }
};

constexpr float LOG2E = 1.4426950408889634f;

__device__ __forceinline__ void load_w(uint32_t (&a)[8][4], uint32_t addr) {
#pragma unroll
    for (int ks = 0; ks < 8; ks++) ldsm4t(a[ks], addr + ks * 2048);
}
__device__ __forceinline__ void load_act(uint32_t (&b)[4][4], uint32_t addr) {
#pragma unroll
    for (int i = 0; i < 4; i++) ldsm4(b[i], addr + i * 64);
}
__device__ __forceinline__ void mma_stage(float (&acc)[4][4], const uint32_t (&a)[8][4], const uint32_t (&b)[4][4]) {
#pragma unroll
    for (int ks = 0; ks < 8; ks++) mma16816(acc[ks & 3], a[ks], b[ks >> 1][2 * (ks & 1)], b[ks >> 1][2 * (ks & 1) + 1]);
}
__device__ __forceinline__ bool mbar_test_cluster(uint32_t bar) {
    uint32_t ok;
    asm volatile("{\n.reg .pred p;\nmbarrier.test_wait.parity.relaxed.cluster.shared::cta.b64 p, [%1], 0;\nselp.u32 %0, 1, 0, p;\n}"
                 : "=r"(ok) : "r"(bar) : "memory");
    return ok;
}

template <int shift>
__global__ void __cluster_dims__(8, 1, 1) __launch_bounds__(THREADS, 1)
fused_decode_kernel(const void* wq, const __nv_bfloat16* __restrict__ x, __nv_bfloat16* __restrict__ out,
                    const uint32_t tau_arg, const uint32_t tau2_arg, const __grid_constant__ Maps maps,
                    const __nv_bfloat16* __restrict__ b1, const __nv_bfloat16* __restrict__ b2) {
    extern __shared__ __align__(1024) uint8_t smem_raw[];
    uint32_t sb;
    asm volatile("{\n.reg .u64 a;\ncvta.to.shared.u64 a, %1;\ncvt.u32.u64 %0, a;\n}" : "=r"(sb) : "l"(smem_raw));
    uint8_t* sp = smem_raw;
    const uint32_t bar_full = sb + SM_BAR, bar_empty = bar_full + 8 * STAGES;
    const uint32_t bar_ok = bar_empty + 8 * STAGES, bar_q = bar_ok + 8, bar_o = bar_q + 8, bar_gate = bar_o + 16;

    if (threadIdx.x == 64 && blockIdx.x < N_ATT)
        asm volatile("cp.async.bulk.prefetch.L2.global [%0], %1;"
                     ::"l"(reinterpret_cast<const char*>(wq) + (size_t)blockIdx.x * PREF_BYTES), "r"(PREF_BYTES) : "memory");
    const int warp_id = __shfl_sync(0xffffffffu, (int)(threadIdx.x >> 5), 0), lane = threadIdx.x & 31;
    const int cta = shift == 0 ? blockIdx.x : blockIdx.x >= shift ? blockIdx.x - shift : blockIdx.x + N_ATT;
    const bool is_att = cta < N_ATT;
    const int hkv = cta >> 3, rank = cta & 7;

    if (warp_id == 0) {
        const bool leader = elect_one();
        uint64_t pol;
        asm volatile("createpolicy.fractional.L2::evict_first.b64 %0, 1.0;" : "=l"(pol));
        const int nt = is_att ? NT_ATT : rank < N_FFN ? NT_FFN : 0;
        const int row0 = (rank * HKV + hkv) * SK - 128;
        auto coords = [&](int i, int& mi, int& c1, int& c2) {
            c2 = 0;
            if (is_att) {
                mi = (i >> 1) & 1; c1 = row0 + (i >> 2) * 128 + (i & 1) * 64;
                if (i >= NT_ATT - 12) { mi = ((i >> 3) & 1) ^ 1; c1 = row0 + 128 + SK - 256 + (i & 3) * 64; }
                if (i < 4) { mi = 2; c1 = 128 * i; c2 = cta; }
                if (i >= NT_ATT - 4) { mi = 3; c1 = 512 * hkv + 128 * (i - (NT_ATT - 4)); c2 = rank; }
            } else {
                mi = 5; c1 = FS * rank + 16 * (i - 16);
                if (i < 16) { mi = 4; c1 = 32 * i; c2 = 4 * rank; }
            }
        };
#pragma unroll
        for (int i = 0; i < D_START; i++)
            if (leader) mbar_init(bar_full + 8 * i, 1);
        asm volatile("fence.mbarrier_init.release.cluster;" ::: "memory");
        if (nt > 0) {
#pragma unroll
            for (int i = 0; i < D_START; i++) {
                int mi, c1, c2;
                coords(i, mi, c1, c2);
                if (leader) {
                    mbar_expect_tx(bar_full + 8 * i, STAGE_BYTES);
                    tma3d(sb + SM_RING + i * STAGE_BYTES, &maps.m[mi], bar_full + 8 * i, c1, c2, pol);
                }
            }
        }
        const uint32_t t0 = timer_ns();
        __syncwarp();
        bar_all();
        if (is_att) cluster_arrive();
        const uint4 taus = lds128(sb + SM_ML + 192);
        const uint32_t tau = taus.x, tau2 = taus.y;
        Cursor cur, lag, hi;
        cur.slot = D_START;
        lag.slot = D_START - D_MIN;
        const uint32_t step = is_att ? tau : tau * FFN_PACE / 16;
        uint32_t due = t0 + step * PACE_OFF / 16;
#pragma unroll 1
        for (int i = D_START; i < nt; i++) {
            int mi, c1, c2;
            coords(i, mi, c1, c2);
            const CUtensorMap* map = &maps.m[mi];
            const uint32_t dst = sb + SM_RING + cur.slot * STAGE_BYTES, bar = bar_full + 8 * cur.slot;
            const uint32_t lbar = is_att ? bar_full + 8 * lag.slot : bar_q, lph = is_att ? lag.phase : 0u;
            if (i >= STAGES) mbar_wait(bar + 8 * STAGES, cur.phase ^ 1u);
            if (leader) mbar_expect_tx(bar, STAGE_BYTES);
            int it = 0;
#pragma unroll 1
            while (!mbar_test(lbar, lph) && (int)(timer_ns() - due) < 0 && ++it < 4096) {}
            if (leader) tma3d(dst, map, bar, c1, c2, pol);
            if (i == I_GATE && leader) mbar_arrive(bar_gate);
            lag.adv(i == NT_ATT - 5 ? 1 + D_MIN - D_WO : 1);
            cur.adv(1);
            due += i >= I_FAST ? tau2 : step;
            if (i == NT_ATT - 5) due += step * WO_GAP / 16;
            if (i >= D_HI) {
                if (!mbar_test(bar_full + 8 * hi.slot, hi.phase)) due += step * SLIP / 16;
                hi.adv(1);
            }
            __syncwarp();
        }
    } else if (warp_id == 1) {
        if (elect_one()) {
            if (sb & 1023u) __trap();
#pragma unroll
            for (int s = D_START; s < STAGES; s++) mbar_init(bar_full + 8 * s, 1);
#pragma unroll
            for (int s = 0; s < STAGES; s++) mbar_init(bar_empty + 8 * s, is_att ? 4 : 8);
            mbar_init(bar_ok, 1);
            mbar_init(bar_q, 1);
            mbar_init(bar_o, 1);
            mbar_init(bar_o + 8, 1);
            mbar_init(bar_gate, 1);
            asm volatile("fence.mbarrier_init.release.cluster;" ::: "memory");
            mbar_expect_tx(bar_q, 1024);
            sts32(sb + SM_ML + 192, tau_arg);
            sts32(sb + SM_ML + 196, tau2_arg);
            mbar_expect_tx(bar_o, 7 * 512);
            mbar_expect_tx(bar_o + 8, 7 * 512);
        }
        __syncwarp();
        bar_all();
        if (is_att) {
            cluster_arrive();
            mbar_wait(bar_gate, 0);
            if (lane == 0) {
                int it = 0;
                while (true) {
                    unsigned v;
                    asm volatile("ld.acquire.gpu.global.u32 %0, [%1];" : "=r"(v) : "l"(&g_ctr) : "memory");
                    if (v >= 8u) break;
                    __nanosleep(200);
                    if (++it > SPIN_LIMIT) __trap();
                }
            }
            __syncwarp();
            const int g = lane >> 2, t = lane & 3;
#pragma unroll 2
            for (int mt = 0; mt < 4; mt++) {
                const int col = rank * 64 + mt * 16 + g;
                float y[4] = {}, res[4];
#pragma unroll
                for (int i = 0; i < N_FFN; i++) {
                    const float4 v = __ldcg(g_gp + ((i * 8 + rank) * 4 + mt) * 32 + lane);
                    y[0] += v.x; y[1] += v.y; y[2] += v.z; y[3] += v.w;
                }
#pragma unroll
                for (int c = 0; c < 4; c++) {
                    const int cc = col + 8 * (c >> 1), bb = 2 * t + (c & 1);
                    const float z = rbf(rbf(y[c]) + __bfloat162float(b2[cc]));
                    y[c] = rbf(__fdividef(z, 1.0f + __expf(-z)));
                    res[c] = bb == hkv ? __bfloat162float(x[bb * DM + cc]) : 0.f;
                }
                *reinterpret_cast<float4*>(sp + SM_GATE + mt * 1024 + lane * 16) = make_float4(y[0], y[1], y[2], y[3]);
                *reinterpret_cast<float4*>(sp + SM_GATE + mt * 1024 + 512 + lane * 16) = make_float4(res[0], res[1], res[2], res[3]);
            }
            __syncwarp();
            if (lane == 0) {
                mbar_arrive(bar_ok);
                atomicInc(&g_ctr, N_CTA - 1);
            }
        } else if (rank == N_FFN) {
#pragma unroll 4
            for (int i = 0; i < 16; i++) reinterpret_cast<uint4*>(out)[i * 32 + lane] = make_uint4(0, 0, 0, 0);
            __syncwarp();
            if (lane == 0) {
                asm volatile("fence.acq_rel.gpu;" ::: "memory");
                atomicInc(&g_ctr, N_CTA - 1);
            }
        }
    } else {
        const int warp = warp_id - 2, tid = threadIdx.x - 64;
        const int g = lane >> 2, t = lane & 3;
        {
            uint4 xv[2];
#pragma unroll
            for (int i = 0; i < 2; i++) xv[i] = __ldg(reinterpret_cast<const uint4*>(x + warp * DM + i * 256 + lane * 8));
            bar_all();
            if (is_att) cluster_arrive();
            uint32_t w[8] = {xv[0].x, xv[0].y, xv[0].z, xv[0].w, xv[1].x, xv[1].y, xv[1].z, xv[1].w};
            float s0 = 0.f, s1 = 0.f;
#pragma unroll
            for (int i = 0; i < 8; i++) { s0 += bf_lo(w[i]); s1 += bf_hi(w[i]); }
            s0 += s1;
#pragma unroll
            for (int o = 16; o > 0; o >>= 1) s0 += __shfl_xor_sync(0xffffffffu, s0, o);
            const float mean = s0 * (1.0f / DM);
            s0 = 0.f; s1 = 0.f;
#pragma unroll
            for (int i = 0; i < 8; i++) {
                const float d0 = bf_lo(w[i]) - mean, d1 = bf_hi(w[i]) - mean;
                s0 += d0 * d0; s1 += d1 * d1;
            }
            s0 += s1;
#pragma unroll
            for (int o = 16; o > 0; o >>= 1) s0 += __shfl_xor_sync(0xffffffffu, s0, o);
            const uint32_t mb = pack_bf16(mean, mean);
            float sd;
            asm("sqrt.approx.f32 %0, %1;" : "=f"(sd) : "f"(rbf(rbf(s0 * (1.0f / DM)) + 1e-5f)));
            const float rs = rcp(rbf(sd));
#pragma unroll
            for (int i = 0; i < 8; i++) {
                const uint32_t d = sub_bf16x2(w[i], mb);
                w[i] = pack_bf16(bf_lo(d) * rs, bf_hi(d) * rs);
            }
#pragma unroll
            for (int i = 0; i < 2; i++)
                *reinterpret_cast<uint4*>(sp + SM_XN + (warp * XN_STRIDE + i * 256 + lane * 8) * 2) =
                    make_uint4(w[4 * i], w[4 * i + 1], w[4 * i + 2], w[4 * i + 3]);
        }
        bar_compute();
        const uint32_t* xn32 = reinterpret_cast<const uint32_t*>(sp + SM_XN) + g * (XN_STRIDE / 2) + t;
        const int krow = (lane & 7) + (lane >> 4) * 8;
        const int cbit = (lane >> 3) & 1;
        const int wq4 = warp & 3;
        Cursor cur;

        if (is_att) {
            cluster_wait();
            const uint32_t wbase = sb + SM_RING + krow * 128 + (((2 * wq4 + cbit) ^ (lane & 7)) << 4);
            const uint32_t abase = sb + SM_XN + (lane & 7) * (XN_STRIDE * 2) + (lane >> 3) * 16;
            if (warp < 4) {
                float acc[4][4] = {};
#pragma unroll 1
                for (int s = 0; s < 4; s++) {
                    uint32_t a[8][4], bf[4][4];
                    load_act(bf, abase + s * 256);
                    mbar_wait(bar_full + 8 * s, 0);
                    load_w(a, wbase + s * STAGE_BYTES);
                    mma_stage(acc, a, bf);
                    __syncwarp();
                    if (lane == 0) mbar_arrive(bar_empty + 8 * s);
                }
                const uint32_t q0 = movm_t(pack_bf16((acc[0][0] + acc[1][0]) + (acc[2][0] + acc[3][0]), (acc[0][1] + acc[1][1]) + (acc[2][1] + acc[3][1])));
                const uint32_t q1 = movm_t(pack_bf16((acc[0][2] + acc[1][2]) + (acc[2][2] + acc[3][2]), (acc[0][3] + acc[1][3]) + (acc[2][3] + acc[3][3])));
                st_async2(mapa(sb + SM_QIN + ((rank * 4 + warp) * 4 + t) * 8, g), q0, q1, mapa(bar_q, g));
            }
            uint2 qf[8];
            mbar_wait_cluster(bar_q, 0);
#pragma unroll
            for (int kk = 0; kk < 8; kk++) qf[kk] = *reinterpret_cast<const uint2*>(sp + SM_QIN + (((g & 3) * 8 + kk) * 4 + t) * 8);
            float o[8][4] = {};
            uint32_t mpk = 0xff7fff7fu;
            float m0 = bf_lo(mpk), m1 = bf_hi(mpk), l0 = 0.f, l1 = 0.f;
            uint32_t koff[4], voff[4];
#pragma unroll
            for (int i = 0; i < 4; i++) {
                koff[i] = (16 * wq4 + (lane & 7) + cbit * 8) * 128 + (((2 * i + (lane >> 4)) ^ (lane & 7)) << 4);
                voff[i] = (16 * wq4 + krow) * 128 + (((2 * i + cbit) ^ (lane & 7)) << 4);
            }
            uint32_t s01, s23, u01 = 0, u23 = 0;
            cur.adv(4 + (warp >> 2));
#pragma unroll 1
            for (int tile = 0;; tile++) {
                const bool last = tile >= KV_TILES / 2 - 2;
                if (tile == KV_TILES / 2 - 3) mbar_wait(bar_ok, 0);
                const uint32_t kbar = bar_full + 8 * cur.slot, vbar = kbar + 16;
                const uint32_t kb = sb + SM_RING + cur.slot * STAGE_BYTES, vb = kb + 2 * STAGE_BYTES;
                uint32_t a[8][4];
                mbar_wait(kbar, cur.phase);
#pragma unroll
                for (int i = 0; i < 8; i++) ldsm4(a[i], kb + (i >> 2) * 8192 + koff[i & 3]);
                const bool early = __all_sync(0xffffffffu, !last && mbar_test(vbar, cur.phase));
                float sa[4][4] = {};
#pragma unroll
                for (int i = 0; i < 8; i++) mma16816(sa[i & 3], a[i], qf[i].x, qf[i].y);
                __syncwarp();
                if (lane == 0) mbar_arrive(kbar + 8 * STAGES);
                if (early) {
#pragma unroll
                    for (int i = 0; i < 8; i++) ldsm4t(a[i], vb + (i >> 2) * 8192 + voff[i & 3]);
                }
                s01 = pack_bf16((sa[0][0] + sa[1][0]) + (sa[2][0] + sa[3][0]), (sa[0][1] + sa[1][1]) + (sa[2][1] + sa[3][1]));
                s23 = pack_bf16((sa[0][2] + sa[1][2]) + (sa[2][2] + sa[3][2]), (sa[0][3] + sa[1][3]) + (sa[2][3] + sa[3][3]));
                const float scale = 0.08838834764831845f;
                s01 = pack_bf16(bf_lo(s01) * scale, bf_hi(s01) * scale);
                s23 = pack_bf16(bf_lo(s23) * scale, bf_hi(s23) * scale);
                if (last) {
                    if (tile == KV_TILES / 2 - 1) break;
                    u01 = s01; u23 = s23;
                    cur.adv(2);
                    continue;
                }
                uint32_t mx = max_bf16x2(max_bf16x2(s01, s23), mpk);
                if (__any_sync(0xffffffffu, mx != mpk)) {
                    mx = max_bf16x2(mx, __shfl_xor_sync(0xffffffffu, mx, 4));
                    mx = max_bf16x2(mx, __shfl_xor_sync(0xffffffffu, mx, 8));
                    mx = max_bf16x2(mx, __shfl_xor_sync(0xffffffffu, mx, 16));
                    const float n0 = bf_lo(mx), n1 = bf_hi(mx);
                    const float a0 = ex2((m0 - n0) * LOG2E), a1 = ex2((m1 - n1) * LOG2E);
                    m0 = n0; m1 = n1; mpk = mx;
                    l0 *= a0; l1 *= a1;
#pragma unroll
                    for (int mt = 0; mt < 8; mt++) { o[mt][0] *= a0; o[mt][1] *= a1; o[mt][2] *= a0; o[mt][3] *= a1; }
                }
                const float p0 = ex2((bf_lo(s01) - m0) * LOG2E), p1 = ex2((bf_hi(s01) - m1) * LOG2E);
                const float p2 = ex2((bf_lo(s23) - m0) * LOG2E), p3 = ex2((bf_hi(s23) - m1) * LOG2E);
                l0 += p0 + p2; l1 += p1 + p3;
                const uint32_t pb0 = movm_t(pack_bf16(p0, p1)), pb1 = movm_t(pack_bf16(p2, p3));
                if (!early) {
                    mbar_wait(vbar, cur.phase);
#pragma unroll
                    for (int i = 0; i < 8; i++) ldsm4t(a[i], vb + (i >> 2) * 8192 + voff[i & 3]);
                }
#pragma unroll
                for (int i = 0; i < 8; i++) mma16816(o[i], a[i], pb0, pb1);
                __syncwarp();
                if (lane == 0) mbar_arrive(vbar + 8 * STAGES);
                cur.adv(4);
            }
            constexpr int SLOT_K = (NT_ATT - 12) % STAGES, SLOT_V = SLOT_K + 4;
            static_assert(SLOT_V + 4 <= STAGES, "last tiles must not wrap");
            constexpr uint32_t PH_LAST = ((NT_ATT - 12) / STAGES) & 1;
            const uint32_t orow = sb + SM_XN + rank * (XN_STRIDE * 2);
            const bool hi = t >= 2;
            {
                uint32_t mx = max_bf16x2(max_bf16x2(max_bf16x2(s01, s23), max_bf16x2(u01, u23)), mpk);
                mx = max_bf16x2(mx, __shfl_xor_sync(0xffffffffu, mx, 4));
                mx = max_bf16x2(mx, __shfl_xor_sync(0xffffffffu, mx, 8));
                mx = max_bf16x2(mx, __shfl_xor_sync(0xffffffffu, mx, 16));
                if (lane < 2) sts32(sb + SM_ML + lane * 32 + warp * 4, mx);
                bar_compute();
                const uint4 ma = lds128(sb + SM_ML + (t & 1) * 32), mb = lds128(sb + SM_ML + (t & 1) * 32 + 16);
                const uint32_t M = max_bf16x2(max_bf16x2(max_bf16x2(ma.x, ma.y), max_bf16x2(ma.z, ma.w)),
                                              max_bf16x2(max_bf16x2(mb.x, mb.y), max_bf16x2(mb.z, mb.w)));
                const float M0 = bf_lo(M), M1 = bf_hi(M);
                const float f0 = ex2((m0 - M0) * LOG2E), f1 = ex2((m1 - M1) * LOG2E);
                l0 *= f0; l1 *= f1;
#pragma unroll
                for (int j = 0; j < 2; j++) {
                    const uint32_t a01 = j ? s01 : u01, a23 = j ? s23 : u23;
                    const float p0 = ex2((bf_lo(a01) - M0) * LOG2E), p1 = ex2((bf_hi(a01) - M1) * LOG2E);
                    const float p2 = ex2((bf_lo(a23) - M0) * LOG2E), p3 = ex2((bf_hi(a23) - M1) * LOG2E);
                    l0 += p0 + p2; l1 += p1 + p3;
                    const uint32_t pb0 = movm_t(pack_bf16(p0, p1)), pb1 = movm_t(pack_bf16(p2, p3));
                    if (lane < 16) *reinterpret_cast<uint2*>(sp + SM_H + lane * 144 + (warp >> 2) * 64 + j * 32 + wq4 * 8) = make_uint2(pb0, pb1);
                }
                uint8_t* part = sp + SM_RING + (SLOT_K + (warp >> 2)) * STAGE_BYTES + wq4 * 2048 + (t >> 1) * 1024 +
                                ((2 * g + (t & 1)) ^ (4 * ((t >> 1) ^ (warp >> 2)))) * 16;
#pragma unroll
                for (int i = 0; i < 4; i++)
                    *reinterpret_cast<float4*>(part + i * 256) =
                        make_float4((hi ? o[4 + i][0] : o[i][0]) * f0, (hi ? o[4 + i][1] : o[i][1]) * f1,
                                    (hi ? o[4 + i][2] : o[i][2]) * f0, (hi ? o[4 + i][3] : o[i][3]) * f1);
#pragma unroll
                for (int of = 4; of < 32; of <<= 1) {
                    l0 += __shfl_xor_sync(0xffffffffu, l0, of);
                    l1 += __shfl_xor_sync(0xffffffffu, l1, of);
                }
                if (lane < 2) *reinterpret_cast<float2*>(sp + SM_ML + 64 + lane * 64 + warp * 8) = make_float2(l0, l1);
            }
            bar_compute();
            {
                uint4 pf[4];
#pragma unroll
                for (int i = 0; i < 4; i++) pf[i] = *reinterpret_cast<const uint4*>(sp + SM_H + (lane & 15) * 144 + (lane >> 4) * 64 + i * 16);
                const uint8_t* psum = sp + SM_RING + (SLOT_K + (t >> 1)) * STAGE_BYTES + warp * 256 +
                                      ((2 * g + (t & 1)) ^ (4 * ((t >> 1) ^ (warp >> 2)))) * 16;
                float acc[4][4];
#pragma unroll
                for (int w = 0; w < 4; w++) {
                    const float4 v = *reinterpret_cast<const float4*>(psum + w * 2048);
                    acc[w][0] = v.x; acc[w][1] = v.y; acc[w][2] = v.z; acc[w][3] = v.w;
                }
                float L0 = 0.f, L1 = 0.f;
#pragma unroll
                for (int i = 0; i < 4; i++) {
                    const float4 v = *reinterpret_cast<const float4*>(sp + SM_ML + 64 + (t & 1) * 64 + i * 16);
                    L0 += v.x + v.z; L1 += v.y + v.w;
                }
                const float i0 = rcp(L0), i1 = rcp(L1);
                const uint32_t vbase = wbase + SLOT_V * STAGE_BYTES + (warp >> 2) * 8192;
                const uint32_t ost = orow + (g & 3) * 256 + warp * 32 + (g >> 2) * 16 + t * 4;
#pragma unroll
                for (int j = 0; j < 4; j++) {
                    uint32_t a[4][4];
                    const bool on = (lane >> 4) == (j & 1);
                    const uint4 pa = pf[j & 2], pb = pf[(j & 2) + 1];
                    mbar_wait(bar_full + 8 * (SLOT_V + j), PH_LAST);
#pragma unroll
                    for (int ks = 0; ks < 4; ks++) ldsm4t(a[ks], vbase + j * STAGE_BYTES + ks * 2048);
                    mma16816(acc[0], a[0], on ? pa.x : 0u, on ? pa.y : 0u);
                    mma16816(acc[1], a[1], on ? pa.z : 0u, on ? pa.w : 0u);
                    mma16816(acc[2], a[2], on ? pb.x : 0u, on ? pb.y : 0u);
                    mma16816(acc[3], a[3], on ? pb.z : 0u, on ? pb.w : 0u);
                }
#pragma unroll
                for (int c = 0; c < 4; c++) { acc[0][c] += acc[2][c]; acc[1][c] += acc[3][c]; }
                const float c0 = acc[0][0] + acc[1][0], c1 = acc[0][1] + acc[1][1], c2 = acc[0][2] + acc[1][2], c3 = acc[0][3] + acc[1][3];
                const float r0 = (hi ? c2 : c0) + __shfl_xor_sync(0xffffffffu, hi ? c0 : c2, 2);
                const float r1 = (hi ? c3 : c1) + __shfl_xor_sync(0xffffffffu, hi ? c1 : c3, 2);
                sts32(ost, movm_t(pack_bf16(r0 * i0, r1 * i1)));
            }
            bar_compute();
            if (warp != rank) {
                const uint4 u0 = lds128(orow + lane * 16), u1 = lds128(orow + lane * 16 + 512);
                const uint32_t odst = mapa(orow + lane * 16, warp), obar = mapa(bar_o, warp);
                st_async4(odst, u0, obar);
                st_async4(odst + 512, u1, obar + 8);
            }
            if (warp < 4) {
                __nv_bfloat16* dst = out + __shfl_sync(0xffffffffu, g * DM + rank * 64 + warp * 16 + 2 * t, lane);
                constexpr uint32_t ph = ((NT_ATT - 4) / STAGES) & 1;
                static_assert((NT_ATT - 4) % STAGES == 0, "wo must start in slot 0");
                uint32_t a[4][8][4], bf[4][4][4];
                float acc[4][4] = {};
                mbar_wait(bar_full, ph);
                load_w(a[0], wbase);
                bool w1;
                int it = 0;
#pragma unroll 1
                while (!(w1 = __all_sync(0xffffffffu, mbar_test(bar_full + 8, ph))) && !__all_sync(0xffffffffu, mbar_test_cluster(bar_o)))
                    if (++it > SPIN_LIMIT) __trap();
                if (w1) load_w(a[1], wbase + STAGE_BYTES);
                mbar_wait_cluster(bar_o, 0);
                load_act(bf[0], abase);
                load_act(bf[1], abase + 256);
                mbar_wait_cluster(bar_o + 8, 0);
                load_act(bf[2], abase + 512);
                load_act(bf[3], abase + 768);
                if (!w1) mbar_wait(bar_full + 8, ph);
                const bool w2 = __all_sync(0xffffffffu, mbar_test(bar_full + 16, ph)), w3 = __all_sync(0xffffffffu, mbar_test(bar_full + 24, ph));
                if (!w1) load_w(a[1], wbase + STAGE_BYTES);
                mma_stage(acc, a[0], bf[0]);
                if (w2) load_w(a[2], wbase + 2 * STAGE_BYTES);
                mma_stage(acc, a[1], bf[1]);
                if (!w2) { mbar_wait(bar_full + 16, ph); load_w(a[2], wbase + 2 * STAGE_BYTES); }
                if (w3) load_w(a[3], wbase + 3 * STAGE_BYTES);
                mma_stage(acc, a[2], bf[2]);
                if (!w3) { mbar_wait(bar_full + 24, ph); load_w(a[3], wbase + 3 * STAGE_BYTES); }
                mma_stage(acc, a[3], bf[3]);
                float r[4];
                const uint4 gt = lds128(sb + SM_GATE + warp * 1024 + lane * 16), rs = lds128(sb + SM_GATE + warp * 1024 + 512 + lane * 16);
#pragma unroll
                for (int c = 0; c < 4; c++) r[c] = (acc[0][c] + acc[1][c]) + (acc[2][c] + acc[3][c]);
                red_bf16x2(dst, movm_t(pack_bf16(fmaf(r[0], __uint_as_float(gt.x), __uint_as_float(rs.x)),
                                                 fmaf(r[1], __uint_as_float(gt.y), __uint_as_float(rs.y)))));
                red_bf16x2(dst + 8, movm_t(pack_bf16(fmaf(r[2], __uint_as_float(gt.z), __uint_as_float(rs.z)),
                                                     fmaf(r[3], __uint_as_float(gt.w), __uint_as_float(rs.w)))));
            }
        } else if (rank < N_FFN) {
            if (tid < FS / 8) *reinterpret_cast<uint4*>(sp + SM_QIN + tid * 16) = __ldg(reinterpret_cast<const uint4*>(b1 + FS * rank) + tid);
            float acc[4][4] = {};
#pragma unroll 1
            for (int kt = 0; kt < 16; kt++) {
                mbar_wait(bar_full + 8 * cur.slot, cur.phase);
                const uint32_t base = sb + SM_RING + cur.slot * STAGE_BYTES + (warp >> 1) * 4096 + krow * 128;
#pragma unroll
                for (int ks = 0; ks < 2; ks++) {
                    const uint32_t b0 = xn32[kt * 16 + ks * 8], b1r = xn32[kt * 16 + ks * 8 + 4];
#pragma unroll
                    for (int mt = 0; mt < 2; mt++) {
                        uint32_t a[4];
                        ldsm4t(a, base + ks * 2048 + (((4 * (warp & 1) + 2 * mt + cbit) ^ (lane & 7)) << 4));
                        mma16816(acc[mt], a, b0, b1r);
                    }
                }
                __syncwarp();
                if (lane == 0) mbar_arrive(bar_empty + 8 * cur.slot);
                cur.adv(1);
            }
            bar_compute();
            __nv_bfloat16* hs = reinterpret_cast<__nv_bfloat16*>(sp + SM_H);
            const __nv_bfloat16* b1s = reinterpret_cast<const __nv_bfloat16*>(sp + SM_QIN);
#pragma unroll
            for (int mt = 0; mt < 2; mt++)
#pragma unroll
                for (int c = 0; c < 4; c++) {
                    const int u = warp * 32 + mt * 16 + g + (c >> 1) * 8;
                    const float hv = rbf(rbf(acc[mt][c]) + __bfloat162float(b1s[u]));
                    const float inner = 0.7978845608028654f * (hv + 0.044715f * hv * hv * hv);
                    hs[(2 * t + (c & 1)) * H_STRIDE + u] = __float2bfloat16_rn(0.5f * hv * (1.0f + tanhf(inner)));
                    acc[mt][c] = 0.f;
                }
            bar_compute();
            const uint32_t* h32 = reinterpret_cast<const uint32_t*>(sp + SM_H) + g * (H_STRIDE / 2) + t;
#pragma unroll 1
            for (int kt = 0; kt < 16; kt++) {
                const uint32_t b0 = h32[kt * 8], b1r = h32[kt * 8 + 4];
                mbar_wait(bar_full + 8 * cur.slot, cur.phase);
                const uint32_t base = sb + SM_RING + cur.slot * STAGE_BYTES + warp * 2048 + krow * 128;
#pragma unroll
                for (int mt = 0; mt < 4; mt++) {
                    uint32_t a[4];
                    ldsm4t(a, base + (((2 * mt + cbit) ^ (lane & 7)) << 4));
                    mma16816(acc[mt], a, b0, b1r);
                }
                __syncwarp();
                if (lane == 0) mbar_arrive(bar_empty + 8 * cur.slot);
                cur.adv(1);
            }
#pragma unroll
            for (int mt = 0; mt < 4; mt++)
                g_gp[((rank * 8 + warp) * 4 + mt) * 32 + lane] = make_float4(acc[mt][0], acc[mt][1], acc[mt][2], acc[mt][3]);
            bar_compute();
            if (tid == 0) {
                asm volatile("fence.acq_rel.gpu;" ::: "memory");
                atomicInc(&g_ctr, N_CTA - 1);
            }
        }
    }
}

typedef CUresult (*EncodeTiledFn)(CUtensorMap*, CUtensorMapDataType, cuuint32_t, void*, const cuuint64_t*, const cuuint64_t*,
                                  const cuuint32_t*, const cuuint32_t*, CUtensorMapInterleave, CUtensorMapSwizzle,
                                  CUtensorMapL2promotion, CUtensorMapFloatOOBfill);

void encode(EncodeTiledFn fn, CUtensorMap* m, const void* ptr, int rows, int cols, int nrow, int nblk, CUtensorMapL2promotion promo) {
    const cuuint64_t dims[3] = {64, (cuuint64_t)rows, (cuuint64_t)cols / 64}, strides[2] = {(cuuint64_t)cols * 2, 128};
    const cuuint32_t box[3] = {64, (cuuint32_t)nrow, (cuuint32_t)nblk}, es[3] = {1, 1, 1};
    fn(m, CU_TENSOR_MAP_DATA_TYPE_BFLOAT16, 3, const_cast<void*>(ptr), dims, strides, box, es,
       CU_TENSOR_MAP_INTERLEAVE_NONE, CU_TENSOR_MAP_SWIZZLE_128B, promo, CU_TENSOR_MAP_FLOAT_OOB_FILL_NONE);
}

}

extern "C" void kernel_launch(void* const* d_in, const int* in_sizes, int n_in, void* d_out, int out_size) {
    (void)in_sizes; (void)n_in; (void)out_size;
    EncodeTiledFn fn = nullptr;
    cudaDriverEntryPointQueryResult qr;
    cudaGetDriverEntryPoint("cuTensorMapEncodeTiled", (void**)&fn, cudaEnableDefault, &qr);
    cudaFuncSetAttribute(fused_decode_kernel<0>, cudaFuncAttributeMaxDynamicSharedMemorySize, SMEM_BYTES);
    cudaFuncSetAttribute(fused_decode_kernel<8>, cudaFuncAttributeMaxDynamicSharedMemorySize, SMEM_BYTES);

    int dev = 0, khz = 0, bits = 0;
    cudaGetDevice(&dev);
    cudaDeviceGetAttribute(&khz, cudaDevAttrMemoryClockRate, dev);
    cudaDeviceGetAttribute(&bits, cudaDevAttrGlobalMemoryBusWidth, dev);
    const double rel = (khz > 0 && bits > 0) ? (2619000.0 * 5120.0) / ((double)khz * bits) : 1.0;
    const uint32_t tau = (uint32_t)(TAU_NS * rel + 0.5), tau2 = (uint32_t)(TAU2_NS * rel + 0.5);

    int nclusters = 0;
    {
        cudaLaunchConfig_t cfg = {};
        cfg.gridDim = dim3(N_CTA); cfg.blockDim = dim3(THREADS); cfg.dynamicSmemBytes = SMEM_BYTES;
        cudaLaunchAttribute at;
        at.id = cudaLaunchAttributeClusterDimension;
        at.val.clusterDim.x = 8; at.val.clusterDim.y = 1; at.val.clusterDim.z = 1;
        cfg.attrs = &at; cfg.numAttrs = 1;
        if (cudaOccupancyMaxActiveClusters(&nclusters, fused_decode_kernel<0>, &cfg) != cudaSuccess) { nclusters = 0; cudaGetLastError(); }
    }
    auto kernel = nclusters >= N_CTA / 8 ? fused_decode_kernel<0> : fused_decode_kernel<8>;

    Maps maps;
    encode(fn, &maps.m[0], d_in[1], NB * HKV * SK, DH, 64, 2, CU_TENSOR_MAP_L2_PROMOTION_L2_256B);
    encode(fn, &maps.m[1], d_in[2], NB * HKV * SK, DH, 64, 2, CU_TENSOR_MAP_L2_PROMOTION_L2_256B);
    encode(fn, &maps.m[2], d_in[3], DM, HQ * DH, 128, 1, CU_TENSOR_MAP_L2_PROMOTION_L2_128B);
    encode(fn, &maps.m[3], d_in[4], HQ * DH, DM, 128, 1, CU_TENSOR_MAP_L2_PROMOTION_L2_128B);
    encode(fn, &maps.m[4], d_in[6], DM, FF, 32, 4, CU_TENSOR_MAP_L2_PROMOTION_L2_256B);
    encode(fn, &maps.m[5], d_in[8], FF, DM, 16, 8, CU_TENSOR_MAP_L2_PROMOTION_L2_256B);
    kernel<<<N_CTA, THREADS, SMEM_BYTES>>>(d_in[3], (const __nv_bfloat16*)d_in[0], (__nv_bfloat16*)d_out, tau, tau2,
                                                        maps, (const __nv_bfloat16*)d_in[7], (const __nv_bfloat16*)d_in[9]);
}
```
